```python
import torch

def _softmax(x, axis=-1):
    return torch.softmax(x, dim=axis)
def _gelu(x):
    return torch.nn.functional.gelu(x, approximate="tanh")
def _silu(x):
    return torch.nn.functional.silu(x)
def _sigmoid(x):
    return torch.sigmoid(x)
def _layernorm(x, axis=-1, eps=1e-5):
    m = x.mean(dim=axis, keepdim=True)
    v = x.var(dim=axis, keepdim=True, unbiased=False)
    return (x - m) / torch.sqrt(v + eps)
def _scatter_add(tgt, idx, src, axis=0):
    return tgt.clone().index_add_(axis, idx, src)
def _segment_sum(src, seg, n):
    out = torch.zeros((n,) + src.shape[1:], dtype=src.dtype)
    return out.index_add_(0, seg, src)
def _pad(x, pw):
    flat = tuple(v for pair in reversed(pw) for v in pair)
    return torch.nn.functional.pad(x, flat)

kernel_name = 'concat_heads__gqa_block_cached__gqa_block_cached__decode'

def setup_inputs():

    _w = (lambda a: (lambda t: t.to(torch.bfloat16) if t.is_floating_point() else t)(torch.as_tensor(a)))
    def _A_setup():
        B, Sq, D = 1, 1, 448
        Hq, Hkv, Sk, Dh = 16, 8, 65536, 256
        assert Hq % Hkv == 0, (Hq, Hkv)
        return {
            "x": _w((lambda *s: torch.randn(*s, dtype=torch.bfloat16) * 0.8)(B, Sq, D)),
            "k_cache": _w((lambda *s: torch.randn(*s, dtype=torch.bfloat16) * 0.8)(B, Hkv, Sk, Dh)),
            "v_cache": _w((lambda *s: torch.randn(*s, dtype=torch.bfloat16) * 0.05)(B, Hkv, Sk, Dh)),
            "wq": _w((lambda *s: torch.randn(*s, dtype=torch.bfloat16) * 0.8)(D, Hq * Dh) * (D ** -0.5)),
            "wo": _w((lambda *s: torch.randn(*s, dtype=torch.bfloat16) * 0.05)(Hq * Dh, D) * ((Hq * Dh) ** -0.5)),
        }
    _A_in = _A_setup()

    def _B_setup():
        B, Sq, D = 1, 1, 448
        Hq, Hkv, Sk, Dh = 16, 8, 65536, 256
        assert Hq % Hkv == 0, (Hq, Hkv)
        return {
            "x": _w((lambda *s: torch.randn(*s, dtype=torch.bfloat16) * 0.8)(B, Sq, D)),
            "k_cache": _w((lambda *s: torch.randn(*s, dtype=torch.bfloat16) * 0.8)(B, Hkv, Sk, Dh)),
            "v_cache": _w((lambda *s: torch.randn(*s, dtype=torch.bfloat16) * 0.05)(B, Hkv, Sk, Dh)),
            "wq": _w((lambda *s: torch.randn(*s, dtype=torch.bfloat16) * 0.8)(D, Hq * Dh) * (D ** -0.5)),
            "wo": _w((lambda *s: torch.randn(*s, dtype=torch.bfloat16) * 0.05)(Hq * Dh, D) * ((Hq * Dh) ** -0.5)),
        }
    _B_in = _B_setup()

    return {
        "A_x": _A_in["x"],
        "A_k_cache": _A_in["k_cache"],
        "A_v_cache": _A_in["v_cache"],
        "A_wq": _A_in["wq"],
        "A_wo": _A_in["wo"],
        "B_x": _B_in["x"],
        "B_k_cache": _B_in["k_cache"],
        "B_v_cache": _B_in["v_cache"],
        "B_wq": _B_in["wq"],
        "B_wo": _B_in["wo"],
    }

def reference(A_x, A_k_cache, A_v_cache, A_wq, A_wo, B_x, B_k_cache, B_v_cache, B_wq, B_wo):
    def _A_ref(x, k_cache, v_cache, wq, wo):
        B, Sq, D = x.shape
        Hq, Dh = 16, 256
        Hkv = k_cache.shape[1]
        rep = Hq // Hkv
        q = (lambda x, *d: x.permute(*d))((x @ wq).reshape(B, Sq, Hq, Dh), 0, 2, 1, 3)
        k = (lambda x, n, axis: torch.repeat_interleave(x, n, dim=axis))(k_cache, rep, axis=1)
        v = (lambda x, n, axis: torch.repeat_interleave(x, n, dim=axis))(v_cache, rep, axis=1)
        scores = torch.einsum("bhqd,bhkd->bhqk", q, k) * (Dh ** -0.5)
        p = _softmax(scores, axis=-1)
        o = torch.einsum("bhqk,bhkd->bhqd", p, v)
        return (lambda x, *d: x.permute(*d))(o, 0, 2, 1, 3).reshape(B, Sq, Hq * Dh) @ wo

    def _B_ref(x, k_cache, v_cache, wq, wo):
        B, Sq, D = x.shape
        Hq, Dh = 16, 256
        Hkv = k_cache.shape[1]
        rep = Hq // Hkv
        q = (lambda x, *d: x.permute(*d))((x @ wq).reshape(B, Sq, Hq, Dh), 0, 2, 1, 3)
        k = (lambda x, n, axis: torch.repeat_interleave(x, n, dim=axis))(k_cache, rep, axis=1)
        v = (lambda x, n, axis: torch.repeat_interleave(x, n, dim=axis))(v_cache, rep, axis=1)
        scores = torch.einsum("bhqd,bhkd->bhqk", q, k) * (Dh ** -0.5)
        p = _softmax(scores, axis=-1)
        o = torch.einsum("bhqk,bhkd->bhqd", p, v)
        return (lambda x, *d: x.permute(*d))(o, 0, 2, 1, 3).reshape(B, Sq, Hq * Dh) @ wo

    a = _A_ref(A_x, A_k_cache, A_v_cache, A_wq, A_wo)
    b = _B_ref(B_x, B_k_cache, B_v_cache, B_wq, B_wo)
    return torch.concatenate([a, b], axis=-1)
```

```cpp
#include <cuda_runtime.h>
#include <cuda_bf16.h>
#include <cuda.h>
#include <stdint.h>

namespace {

constexpr int G = 132;
constexpr int W = 4;
constexpr int NTHREADS = (W + 2) * 32;
constexpr int TILE_BYTES = 8192;
constexpr int STAGE_BYTES = 2 * TILE_BYTES;
constexpr int TOTAL = 65536;
constexpr int DM = 448;
constexpr int SEG_BYTES = 8 * DM * 2;
constexpr int SLOT_STRIDE = 272;
#define K0 2
#define START_DELAY 2500
#define WO_LAG 0
#define MERGE_DELAY 1536
constexpr unsigned SPIN_LIMIT = 1u << 24;

struct Params {
    CUtensorMap km[2];
    CUtensorMap vm[2];
    const __nv_bfloat16* x[2];
    const __nv_bfloat16* wq[2];
    const __nv_bfloat16* wo[2];
    __nv_bfloat16* out;
};

__device__ unsigned int g_epoch;
__device__ unsigned int g_ticket;
__device__ ulonglong2 g_q[16 * 2 * 16 * 4];
__device__ ulonglong2 g_po[16 * 64 * G * 4];
__device__ ulonglong2 g_pml[16 * G * 2];
__device__ ulonglong2 g_ol[2 * 56 * 64 * 4];

#define STAMP(i)

__device__ __forceinline__ uint32_t smem_u32(const void* p) { return (uint32_t)__cvta_generic_to_shared(p); }
__device__ __forceinline__ void mbar_init(uint32_t bar, uint32_t cnt) {
    asm volatile("mbarrier.init.shared::cta.b64 [%0], %1;" ::"r"(bar), "r"(cnt) : "memory");
}
__device__ __forceinline__ void mbar_expect_tx(uint32_t bar, uint32_t bytes) {
    asm volatile("mbarrier.arrive.expect_tx.shared::cta.b64 _, [%0], %1;" ::"r"(bar), "r"(bytes) : "memory");
}
__device__ __forceinline__ void mbar_arrive(uint32_t bar) {
    asm volatile("mbarrier.arrive.shared::cta.b64 _, [%0];" ::"r"(bar) : "memory");
}
__device__ __forceinline__ bool mbar_try(uint32_t bar, uint32_t parity) {
    uint32_t ok;
    asm volatile("{\n.reg .pred p;\nmbarrier.try_wait.parity.shared::cta.b64 p, [%1], %2;\nselp.u32 %0, 1, 0, p;\n}"
                 : "=r"(ok) : "r"(bar), "r"(parity) : "memory");
    return ok != 0;
}
__device__ __forceinline__ void mbar_wait(uint32_t bar, uint32_t parity) {
    if (mbar_try(bar, parity)) return;
    unsigned n = 0;
    while (!mbar_try(bar, parity)) {
        if (++n > SPIN_LIMIT) __trap();
    }
}
__device__ __forceinline__ void tma3d(uint32_t dst, const CUtensorMap* m, int row, uint32_t bar, uint64_t pol) {
    asm volatile(
        "cp.async.bulk.tensor.3d.shared::cluster.global.mbarrier::complete_tx::bytes.L2::cache_hint "
        "[%0], [%1, {%3, %4, %3}], [%2], %5;" ::"r"(dst), "l"(m), "r"(bar), "r"(0), "r"(row), "l"(pol)
        : "memory");
}
__device__ __forceinline__ void bulk_load(uint32_t dst, const void* src, uint32_t bytes, uint32_t bar, uint64_t pol) {
    asm volatile(
        "cp.async.bulk.shared::cluster.global.mbarrier::complete_tx::bytes.L2::cache_hint [%0], [%1], %2, [%3], %4;"
        ::"r"(dst), "l"(src), "r"(bytes), "r"(bar), "l"(pol) : "memory");
}
__device__ __forceinline__ void ldsm4(uint32_t (&r)[4], uint32_t addr) {
    asm volatile("ldmatrix.sync.aligned.m8n8.x4.shared.b16 {%0,%1,%2,%3}, [%4];"
                 : "=r"(r[0]), "=r"(r[1]), "=r"(r[2]), "=r"(r[3]) : "r"(addr) : "memory");
}
__device__ __forceinline__ void ldsm4t(uint32_t (&r)[4], uint32_t addr) {
    asm volatile("ldmatrix.sync.aligned.m8n8.x4.trans.shared.b16 {%0,%1,%2,%3}, [%4];"
                 : "=r"(r[0]), "=r"(r[1]), "=r"(r[2]), "=r"(r[3]) : "r"(addr) : "memory");
}
__device__ __forceinline__ void mma16816(float (&c)[4], const uint32_t (&a)[4], uint32_t b0, uint32_t b1) {
    asm volatile("mma.sync.aligned.m16n8k16.row.col.f32.bf16.bf16.f32 {%0,%1,%2,%3}, {%4,%5,%6,%7}, {%8,%9}, {%0,%1,%2,%3};"
                 : "+f"(c[0]), "+f"(c[1]), "+f"(c[2]), "+f"(c[3])
                 : "r"(a[0]), "r"(a[1]), "r"(a[2]), "r"(a[3]), "r"(b0), "r"(b1));
}
__device__ __forceinline__ uint32_t movtrans(uint32_t a) {
    uint32_t d;
    asm volatile("movmatrix.sync.aligned.m8n8.trans.b16 %0, %1;" : "=r"(d) : "r"(a));
    return d;
}
__device__ __forceinline__ float ex2(float x) {
    float y;
    asm("ex2.approx.ftz.f32 %0, %1;" : "=f"(y) : "f"(x));
    return y;
}
__device__ __forceinline__ uint32_t pack_bf16(float lo, float hi) {
    uint32_t d;
    asm("cvt.rn.bf16x2.f32 %0, %1, %2;" : "=r"(d) : "f"(hi), "f"(lo));
    return d;
}
__device__ __forceinline__ float bf_lo(uint32_t v) { return __uint_as_float(v << 16); }
__device__ __forceinline__ float bf_hi(uint32_t v) { return __uint_as_float(v & 0xffff0000u); }
__device__ __forceinline__ float round_bf16(float v) { return bf_lo(pack_bf16(v, 0.f)); }

__device__ __forceinline__ void ll_store(ulonglong2* p, uint32_t a, uint32_t b, uint32_t tag) {
    unsigned long long x = ((unsigned long long)tag << 32) | a;
    unsigned long long y = ((unsigned long long)tag << 32) | b;
    asm volatile("st.relaxed.gpu.global.v2.b64 [%0], {%1, %2};" ::"l"(p), "l"(x), "l"(y) : "memory");
}
__device__ __forceinline__ bool ll_load(const ulonglong2* p, uint32_t& a, uint32_t& b, uint32_t tag) {
    unsigned long long x, y;
    asm volatile("ld.relaxed.gpu.global.v2.b64 {%0, %1}, [%2];" : "=l"(x), "=l"(y) : "l"(p) : "memory");
    a = (uint32_t)x;
    b = (uint32_t)y;
    return ((uint32_t)(x >> 32) == tag) & ((uint32_t)(y >> 32) == tag);
}

template <int NS>
struct Smem {
    static constexpr int RING = 0;
    static constexpr int SLOTS = NS * STAGE_BYTES;
    static constexpr int SLOTML = SLOTS + W * 2 * SLOT_STRIDE * 4;
    static constexpr int RED = SLOTML + W * 16;
    static constexpr int OFIN = RED + W * DM * 4;
    static constexpr int Q0 = OFIN + 64 * 4;
    static constexpr int TK = Q0 + 128 * 8;
    static constexpr int BARS = TK + 32 * 4;
    static constexpr int NBARS = 2 * NS + 6;
    static constexpr int SIZE = BARS + NBARS * 8;
};

template <int NS>
__global__ void __launch_bounds__(NTHREADS, (NS <= 4 ? 2 : 1)) fused_decode_kernel(const __grid_constant__ Params p) {
    extern __shared__ __align__(1024) unsigned char smem_raw[];
    using L = Smem<NS>;
    static_assert(NS % W == 0 && K0 < NS, "ring geometry");
    unsigned char* smem = smem_raw;
    const uint32_t sbase = smem_u32(smem);
    const int warp = threadIdx.x >> 5, lane = threadIdx.x & 31;
    const int cta = blockIdx.x;
    const bool has_task = cta < 128;
    const int tb = cta >> 6, slice = cta & 63;

    const uint32_t bar_full = sbase + L::BARS;
    const uint32_t bar_empty = bar_full + NS * 8;
    const uint32_t bar_sfull = bar_empty + NS * 8;
    const uint32_t bar_sempty = bar_sfull + 8;
    const uint32_t bar_ofin = bar_sempty + 8;
    const uint32_t bar_red = bar_ofin + 8;
    const uint32_t bar_wo = bar_red + 8;
    const uint32_t bar_q = bar_wo + 8;
    volatile int* s_tk = reinterpret_cast<volatile int*>(smem + L::TK);
    float* s_slots = reinterpret_cast<float*>(smem + L::SLOTS);
    float* s_slotml = reinterpret_cast<float*>(smem + L::SLOTML);
    float* s_red = reinterpret_cast<float*>(smem + L::RED);
    float* s_ofin = reinterpret_cast<float*>(smem + L::OFIN);
    uint2* s_q0 = reinterpret_cast<uint2*>(smem + L::Q0);

    if (warp == W) {
        uint64_t pol = 0;
        auto issue = [&](int s, int t) {
            s_tk[s] = t;
            s_tk[30] = t;
            const uint32_t bar = bar_full + s * 8;
            const uint32_t dst = sbase + L::RING + s * STAGE_BYTES;
            mbar_expect_tx(bar, STAGE_BYTES);
            const int b = t >> 15, row = (t & 32767) << 4;
            tma3d(dst, &p.km[b], row, bar, pol);
            tma3d(dst + TILE_BYTES, &p.vm[b], row, bar, pol);
        };
        if (lane == 0) {
            STAMP(0);
            for (int s = 0; s < NS; s++) { mbar_init(bar_full + s * 8, 1); mbar_init(bar_empty + s * 8, 1); }
            mbar_init(bar_sfull, W);
            mbar_init(bar_sempty, 1);
            mbar_init(bar_ofin, 1);
            mbar_init(bar_red, W);
            mbar_init(bar_wo, 1);
            mbar_init(bar_q, 1);
            asm volatile("fence.mbarrier_init.release.cluster;" ::: "memory");
            asm volatile("createpolicy.fractional.L2::evict_first.b64 %0, 1.0;" : "=l"(pol));
        }
        __syncwarp();
        asm volatile("bar.arrive 2, %0;" ::"n"(NTHREADS) : "memory");
        if (lane == 0) {
            if (START_DELAY > 0 && has_task) {
                const long long t0 = clock64();
                while (clock64() - t0 < START_DELAY) { }
            }
            STAMP(1);
            for (int i = 0; i < K0; i++) issue(i, cta + G * i);
            int s = K0;
            uint32_t ph = 1;
            while (true) {
                mbar_wait(bar_empty + s * 8, ph);
                const int t = (int)atomicAdd(&g_ticket, 1u) + G * K0;
                if (t >= TOTAL) break;
                issue(s, t);
                if (++s == NS) { s = 0; ph ^= 1; }
            }
            STAMP(2);
            s_tk[30] = 1 << 30;
            s_tk[31] = s;
            const int s0 = s;
            int sl = s - 1 - WO_LAG;
            uint32_t pl = ph ^ 1;
            if (sl < 0) { sl += NS; pl ^= 1; }
#pragma unroll 1
            for (int j = 0; j < W; j++) {
                if (j > 0) mbar_wait(bar_empty + s * 8, ph);
                s_tk[s] = TOTAL;
                mbar_arrive(bar_full + s * 8);
                if (++s == NS) { s = 0; ph ^= 1; }
            }
            if (has_task) {
                mbar_expect_tx(bar_wo, 8 * SEG_BYTES);
                if (WO_LAG < NS - W) mbar_wait(bar_full + sl * 8, pl);
                STAMP(9);
                const char* wo = reinterpret_cast<const char*>(p.wo[tb]) + (size_t)slice * SEG_BYTES;
                s = s0;
#pragma unroll 1
                for (int j = 0; j < 4; j++) {
                    const uint32_t dst = sbase + L::RING + s * STAGE_BYTES;
                    bulk_load(dst, wo + (size_t)(2 * j) * 512 * DM * 2, SEG_BYTES, bar_wo, pol);
                    bulk_load(dst + SEG_BYTES, wo + (size_t)(2 * j + 1) * 512 * DM * 2, SEG_BYTES, bar_wo, pol);
                    if (++s == NS) s = 0;
                }
            }
        }
    } else if (warp == W + 1) {
        uint32_t tag;
        asm volatile("ld.relaxed.gpu.global.u32 %0, [%1];" : "=r"(tag) : "l"(&g_epoch) : "memory");
        tag += 1;
        {
            unsigned n = 0;
            bool synced = false;
            uint32_t qa[4], qb[4];
            while (true) {
                bool ok = true;
#pragma unroll
                for (int i = 0; i < 4; i++) ok &= ll_load(g_q + i * 32 + lane, qa[i], qb[i], tag);
                if (!synced) { asm volatile("bar.sync 2, %0;" ::"n"(NTHREADS) : "memory"); synced = true; }
                if (__all_sync(0xffffffffu, ok)) break;
                if (++n > SPIN_LIMIT) __trap();
            }
#pragma unroll
            for (int i = 0; i < 4; i++) s_q0[i * 32 + lane] = make_uint2(qa[i], qb[i]);
            __syncwarp();
            if (lane == 0) mbar_arrive(bar_q);
        }
        const int qh = slice >> 5;
#pragma unroll 1
        for (int h = 0; h < 16; h++) {
            mbar_wait(bar_sfull, h & 1);
            if (lane == 0) STAMP(16 + h);
            float f0[W], f1[W], M0 = -INFINITY, M1 = -INFINITY, L0 = 0.f, L1 = 0.f;
            float4 ml[W];
#pragma unroll
            for (int w = 0; w < W; w++) {
                ml[w] = *reinterpret_cast<const float4*>(s_slotml + w * 4);
                M0 = fmaxf(M0, ml[w].x);
                M1 = fmaxf(M1, ml[w].z);
            }
            const float R0 = (M0 == -INFINITY) ? 0.f : M0, R1 = (M1 == -INFINITY) ? 0.f : M1;
#pragma unroll
            for (int w = 0; w < W; w++) {
                f0[w] = ex2(ml[w].x - R0);
                f1[w] = ex2(ml[w].z - R1);
                L0 += f0[w] * ml[w].y;
                L1 += f1[w] * ml[w].w;
            }
            ulonglong2* po = g_po + ((size_t)(h * 64 + (lane >> 2)) * G + cta) * 4 + (lane & 3);
            constexpr int PO_JSTRIDE = 8 * G * 4;
#pragma unroll
            for (int j = 0; j < 8; j++) {
                float vx = 0.f, vy = 0.f;
#pragma unroll
                for (int w = 0; w < W; w++) {
                    const float2 v = *reinterpret_cast<const float2*>(
                        s_slots + (w * 2 + (j >> 2)) * SLOT_STRIDE + ((64 * j) & 255) + 2 * lane);
                    const float f = (j < 4) ? f0[w] : f1[w];
                    vx += f * v.x;
                    vy += f * v.y;
                }
                ll_store(po + (size_t)j * PO_JSTRIDE, __float_as_uint(vx), __float_as_uint(vy), tag);
            }
            if (lane < 2)
                ll_store(g_pml + (h * G + cta) * 2 + lane, __float_as_uint(lane ? M1 : M0),
                         __float_as_uint(lane ? L1 : L0), tag);
            __syncwarp();
            if (lane == 0) mbar_arrive(bar_sempty);
            if (h == 13) {
                ulonglong2* pn = po + 2 * 64 * G * 4;
#pragma unroll
                for (int j = 0; j < 8; j++) ll_store(pn + (size_t)j * PO_JSTRIDE, 0u, 0u, tag - 1);
                if (lane < 2) ll_store(g_pml + (15 * G + cta) * 2 + lane, 0u, 0u, tag - 1);
                if (has_task) {
                    ulonglong2* dst = g_ol + ((size_t)(tb * 56 + (lane >> 2)) * 64 + slice) * 4 + (lane & 3);
#pragma unroll
                    for (int j = 0; j < 7; j++) ll_store(dst + (size_t)j * 8 * 64 * 4, 0u, 0u, tag - 1);
                }
            }
            if (has_task && (h >> 3) == tb) {
                const int hm = h;
                if (h < 15) {
                    unsigned n = 0;
                    while (s_tk[30] < (h + 1) * 4096 + MERGE_DELAY) {
                        __nanosleep(200);
                        if (++n > SPIN_LIMIT) __trap();
                    }
                }
                uint32_t mm[5], ll[5], ox[17], oy[17];
                const ulonglong2* pml = g_pml + (hm * G + lane) * 2 + qh;
                const ulonglong2* pr = g_po + (size_t)(hm * 64 + slice) * G * 4 + lane;
                constexpr int PR_STRIDE = 32;
                unsigned n = 0;
                while (true) {
                    bool ok = true;
#pragma unroll
                    for (int j = 0; j < 4; j++) ok &= ll_load(pml + j * 64, mm[j], ll[j], tag);
                    mm[4] = 0xff800000u; ll[4] = 0u;
                    if (lane < G - 128) ok &= ll_load(pml + 4 * 64, mm[4], ll[4], tag);
#pragma unroll
                    for (int it = 0; it < 16; it++) ok &= ll_load(pr + it * PR_STRIDE, ox[it], oy[it], tag);
                    ox[16] = 0u; oy[16] = 0u;
                    if (lane < (G - 128) * 4) ok &= ll_load(pr + 16 * PR_STRIDE, ox[16], oy[16], tag);
                    if (__all_sync(0xffffffffu, ok)) break;
                    if (hm != 15) __nanosleep(400);
                    if (++n > SPIN_LIMIT) __trap();
                }
                if (lane == 0) STAMP(32 + hm);
                float M = -INFINITY;
#pragma unroll
                for (int j = 0; j < 5; j++) M = fmaxf(M, __uint_as_float(mm[j]));
#pragma unroll
                for (int o = 16; o >= 1; o >>= 1) M = fmaxf(M, __shfl_xor_sync(0xffffffffu, M, o));
                float wc[5], Ls = 0.f;
#pragma unroll
                for (int j = 0; j < 5; j++) {
                    wc[j] = ex2(__uint_as_float(mm[j]) - M);
                    Ls += wc[j] * __uint_as_float(ll[j]);
                }
                float ax = 0.f, ay = 0.f;
#pragma unroll
                for (int it = 0; it < 17; it++) {
                    const float wv = __shfl_sync(0xffffffffu, wc[it >> 2], (8 * it + (lane >> 2)) & 31);
                    ax += wv * __uint_as_float(ox[it]);
                    ay += wv * __uint_as_float(oy[it]);
                }
#pragma unroll
                for (int o = 16; o >= 1; o >>= 1) Ls += __shfl_xor_sync(0xffffffffu, Ls, o);
#pragma unroll
                for (int o = 4; o <= 16; o <<= 1) {
                    ax += __shfl_xor_sync(0xffffffffu, ax, o);
                    ay += __shfl_xor_sync(0xffffffffu, ay, o);
                }
                if (lane < 4) {
                    const float inv = 1.0f / Ls;
                    *reinterpret_cast<float2*>(s_ofin + (hm & 7) * 8 + 2 * lane) =
                        make_float2(round_bf16(ax * inv), round_bf16(ay * inv));
                }
                __syncwarp();
                if ((hm & 7) == 6 && lane == 0) mbar_arrive(bar_ofin);
                if (hm == 15 && cta == 64 && lane == 0) {
                    asm volatile("st.relaxed.gpu.global.u32 [%0], %1;" ::"l"(&g_ticket), "r"(0u) : "memory");
                    asm volatile("st.relaxed.gpu.global.u32 [%0], %1;" ::"l"(&g_epoch), "r"(tag) : "memory");
                }
            }
        }
        if (has_task) {
            if (lane == 0) STAMP(3);
            mbar_wait(bar_wo, 0);
            if (lane == 0) STAMP(4);
            int ws = s_tk[31] + 3;
            if (ws >= NS) ws -= NS;
            const uint32_t* wseg = reinterpret_cast<const uint32_t*>(smem + L::RING + ws * STAGE_BYTES + SEG_BYTES);
            float a[7][2];
#pragma unroll
            for (int j = 0; j < 7; j++) { a[j][0] = 0.f; a[j][1] = 0.f; }
#pragma unroll
            for (int r = 0; r < 8; r++) {
                const float o = s_ofin[56 + r];
#pragma unroll
                for (int j = 0; j < 7; j++) {
                    const uint32_t wv = wseg[r * (DM / 2) + 32 * j + lane];
                    a[j][0] += o * bf_lo(wv);
                    a[j][1] += o * bf_hi(wv);
                }
            }
            mbar_wait(bar_red, 0);
            if (lane == 0) STAMP(5);
            ulonglong2* dst = g_ol + ((size_t)(tb * 56 + (lane >> 2)) * 64 + slice) * 4 + (lane & 3);
#pragma unroll
            for (int j = 0; j < 7; j++) {
#pragma unroll
                for (int w = 0; w < W; w++) {
                    const float2 v = *reinterpret_cast<const float2*>(s_red + w * DM + 64 * j + 2 * lane);
                    a[j][0] += v.x;
                    a[j][1] += v.y;
                }
                ll_store(dst + (size_t)j * 8 * 64 * 4, __float_as_uint(a[j][0]), __float_as_uint(a[j][1]), tag);
            }
        }
    } else {
        uint32_t tag;
        asm volatile("ld.relaxed.gpu.global.u32 %0, [%1];" : "=r"(tag) : "l"(&g_epoch) : "memory");
        const int g = lane >> 2, t4 = lane & 3;
        if (has_task) {
            const int r = threadIdx.x >> 3, c8 = threadIdx.x & 7;
            const uint4* wq = reinterpret_cast<const uint4*>(p.wq[tb] + (size_t)(28 * r) * 4096 + slice * 64 + c8 * 8);
            const uint2* xp = reinterpret_cast<const uint2*>(p.x[tb] + 28 * r);
            uint4 wv[28];
            uint2 xv[7];
#pragma unroll
            for (int i = 0; i < 28; i++)
                asm volatile("ld.global.nc.L1::no_allocate.v4.u32 {%0,%1,%2,%3}, [%4];"
                             : "=r"(wv[i].x), "=r"(wv[i].y), "=r"(wv[i].z), "=r"(wv[i].w) : "l"(wq + (size_t)i * 512));
#pragma unroll
            for (int i = 0; i < 7; i++)
                asm volatile("ld.global.nc.v2.u32 {%0,%1}, [%2];" : "=r"(xv[i].x), "=r"(xv[i].y) : "l"(xp + i));
            float acc[8];
#pragma unroll
            for (int j = 0; j < 8; j++) acc[j] = 0.f;
#pragma unroll
            for (int i = 0; i < 28; i++) {
                const uint32_t xw = (i & 2) ? xv[i >> 2].y : xv[i >> 2].x;
                const float xs = (i & 1) ? bf_hi(xw) : bf_lo(xw);
                acc[0] += xs * bf_lo(wv[i].x); acc[1] += xs * bf_hi(wv[i].x);
                acc[2] += xs * bf_lo(wv[i].y); acc[3] += xs * bf_hi(wv[i].y);
                acc[4] += xs * bf_lo(wv[i].z); acc[5] += xs * bf_hi(wv[i].z);
                acc[6] += xs * bf_lo(wv[i].w); acc[7] += xs * bf_hi(wv[i].w);
            }
#pragma unroll
            for (int j = 0; j < 8; j++) {
                acc[j] += __shfl_xor_sync(0xffffffffu, acc[j], 8);
                acc[j] += __shfl_xor_sync(0xffffffffu, acc[j], 16);
            }
            if (lane < 8) {
                float4* d = reinterpret_cast<float4*>(s_red + warp * 64 + lane * 8);
                d[0] = make_float4(acc[0], acc[1], acc[2], acc[3]);
                d[1] = make_float4(acc[4], acc[5], acc[6], acc[7]);
            }
            asm volatile("bar.sync 1, %0;" ::"n"(W * 32) : "memory");
            if (threadIdx.x < 16) {
                const int il = threadIdx.x >> 2;
                float q[4];
#pragma unroll
                for (int k = 0; k < 4; k++) {
                    const int d = 16 * il + 2 * t4 + (k & 1) + 8 * (k >> 1);
                    q[k] = 0.f;
#pragma unroll
                    for (int w = 0; w < W; w++) q[k] += s_red[w * 64 + d];
                }
                ll_store(g_q + ((tb * 16 + (slice >> 2)) * 16 + (slice & 3) * 4 + il) * 4 + t4,
                         pack_bf16(q[0], q[1]), pack_bf16(q[2], q[3]), tag + 1);
            }
            if (threadIdx.x == 0) STAMP(6);
        }
        asm volatile("bar.sync 2, %0;" ::"n"(NTHREADS) : "memory");
        tag += 1;

        float acc[16][4];
#pragma unroll
        for (int i = 0; i < 16; i++) { acc[i][0] = 0.f; acc[i][1] = 0.f; acc[i][2] = 0.f; acc[i][3] = 0.f; }
        float m0 = -INFINITY, m1 = -INFINITY, l0 = 0.f, l1 = 0.f;
        uint32_t qf[16][2];
        int cur = 0;
        const uint32_t krow = (lane & 7) + 8 * ((lane >> 3) & 1), vrow = (lane & 7) + 8 * (lane >> 4);
        const uint32_t koff = krow * 128 + (((lane >> 4) ^ (krow & 7)) << 4);
        const uint32_t voff = TILE_BYTES + vrow * 128 + ((((lane >> 3) & 1) ^ (vrow & 7)) << 4);
        const float SC = 0.0625f * 1.4426950408889634f;
        int s = warp;
        uint32_t ph = 0;
        mbar_wait(bar_q, 0);
#pragma unroll
        for (int i = 0; i < 16; i++) {
            const uint2 v = s_q0[((g & 1) * 16 + i) * 4 + t4];
            qf[i][0] = v.x;
            qf[i][1] = v.y;
        }
        if (threadIdx.x == 0) STAMP(7);
        while (true) {
            mbar_wait(bar_full + s * 8, ph);
            const int t = s_tk[s];
            const int h = t >> 12;
            if (h != cur) {
                while (cur < h) {
#pragma unroll
                    for (int o = 4; o <= 16; o <<= 1) {
                        l0 += __shfl_xor_sync(0xffffffffu, l0, o);
                        l1 += __shfl_xor_sync(0xffffffffu, l1, o);
                    }
                    mbar_wait(bar_sempty, (cur & 1) ^ 1);
                    float* sl = s_slots + (warp * 2 + (t4 & 1)) * SLOT_STRIDE + g + 8 * (t4 >> 1);
#pragma unroll
                    for (int i = 0; i < 16; i++) {
                        const float va = (t4 & 2) ? acc[i][2] : acc[i][0];
                        const float vb = (t4 & 2) ? acc[i][3] : acc[i][1];
                        sl[16 * i] = (t4 & 1) ? vb : va;
                        acc[i][0] = 0.f; acc[i][1] = 0.f; acc[i][2] = 0.f; acc[i][3] = 0.f;
                    }
                    if (lane == 0) *reinterpret_cast<float4*>(s_slotml + warp * 4) = make_float4(m0, l0, m1, l1);
                    __syncwarp();
                    if (lane == 0) mbar_arrive(bar_sfull);
                    m0 = -INFINITY; m1 = -INFINITY; l0 = 0.f; l1 = 0.f;
                    cur++;
                }
                if (h >= 16) break;
                const ulonglong2* qp = g_q + ((h * 2 + (g & 1)) * 16) * 4 + t4;
                unsigned n = 0;
                while (true) {
                    bool ok = true;
#pragma unroll
                    for (int i = 0; i < 16; i++) ok &= ll_load(qp + i * 4, qf[i][0], qf[i][1], tag);
                    if (__all_sync(0xffffffffu, ok)) break;
                    if (++n > SPIN_LIMIT) __trap();
                }
            }
            const uint32_t stage = sbase + L::RING + s * STAGE_BYTES;
            float sc[4][4];
#pragma unroll
            for (int c = 0; c < 4; c++) { sc[c][0] = 0.f; sc[c][1] = 0.f; sc[c][2] = 0.f; sc[c][3] = 0.f; }
            const uint32_t kb = stage + koff;
#pragma unroll
            for (int i = 0; i < 16; i++) {
                uint32_t a[4];
                ldsm4(a, (kb ^ ((i & 3) << 5)) + (i >> 2) * 2048);
                mma16816(sc[i & 3], a, qf[i][0], qf[i][1]);
            }
            const float s0 = ((sc[0][0] + sc[1][0]) + (sc[2][0] + sc[3][0])) * SC;
            const float s1 = ((sc[0][1] + sc[1][1]) + (sc[2][1] + sc[3][1])) * SC;
            const float s2 = ((sc[0][2] + sc[1][2]) + (sc[2][2] + sc[3][2])) * SC;
            const float s3 = ((sc[0][3] + sc[1][3]) + (sc[2][3] + sc[3][3])) * SC;
            float n0 = fmaxf(s0, s2), n1 = fmaxf(s1, s3);
            if (__any_sync(0xffffffffu, (n0 > m0) | (n1 > m1))) {
#pragma unroll
                for (int o = 4; o <= 16; o <<= 1) {
                    n0 = fmaxf(n0, __shfl_xor_sync(0xffffffffu, n0, o));
                    n1 = fmaxf(n1, __shfl_xor_sync(0xffffffffu, n1, o));
                }
                n0 = fmaxf(n0, m0);
                n1 = fmaxf(n1, m1);
                const float f0 = ex2(m0 - n0), f1 = ex2(m1 - n1);
                m0 = n0; m1 = n1;
                l0 *= f0; l1 *= f1;
#pragma unroll
                for (int i = 0; i < 16; i++) { acc[i][0] *= f0; acc[i][1] *= f1; acc[i][2] *= f0; acc[i][3] *= f1; }
            }
            const float p0 = ex2(s0 - m0), p1 = ex2(s1 - m1), p2 = ex2(s2 - m0), p3 = ex2(s3 - m1);
            l0 += p0 + p2;
            l1 += p1 + p3;
            const uint32_t b0 = movtrans(pack_bf16(p0, p1));
            const uint32_t b1 = movtrans(pack_bf16(p2, p3));
            const uint32_t vb = stage + voff;
#pragma unroll
            for (int i = 0; i < 16; i++) {
                uint32_t a[4];
                ldsm4t(a, (vb ^ ((i & 3) << 5)) + (i >> 2) * 2048);
                mma16816(acc[i], a, b0, b1);
            }
            __syncwarp();
            if (lane == 0) mbar_arrive(bar_empty + s * 8);
            s += W;
            if (s >= NS) { s -= NS; ph ^= 1; }
        }

        if (has_task) {
            mbar_wait(bar_ofin, 0);
            mbar_wait(bar_wo, 0);
            const int ws0 = s_tk[31];
            float a[7][2];
#pragma unroll
            for (int j = 0; j < 7; j++) { a[j][0] = 0.f; a[j][1] = 0.f; }
#pragma unroll 1
            for (int hk = warp; hk < 7; hk += W) {
                int ws = ws0 + (hk >> 1);
                if (ws >= NS) ws -= NS;
                const uint32_t* wseg =
                    reinterpret_cast<const uint32_t*>(smem + L::RING + ws * STAGE_BYTES + (hk & 1) * SEG_BYTES);
#pragma unroll
                for (int r = 0; r < 8; r++) {
                    const float o = s_ofin[hk * 8 + r];
#pragma unroll
                    for (int j = 0; j < 7; j++) {
                        const uint32_t wv = wseg[r * (DM / 2) + 32 * j + lane];
                        a[j][0] += o * bf_lo(wv);
                        a[j][1] += o * bf_hi(wv);
                    }
                }
            }
#pragma unroll
            for (int j = 0; j < 7; j++)
                *reinterpret_cast<float2*>(s_red + warp * DM + 64 * j + 2 * lane) = make_float2(a[j][0], a[j][1]);
            __syncwarp();
            if (lane == 0) mbar_arrive(bar_red);
        }
        if (warp == 0 && cta < 112) {
            const ulonglong2* src = g_ol + (size_t)cta * 64 * 4 + lane;
            uint32_t vx[8], vy[8];
            unsigned n = 0;
            while (true) {
                bool ok = true;
#pragma unroll
                for (int i = 0; i < 8; i++) ok &= ll_load(src + i * 32, vx[i], vy[i], tag);
                if (__all_sync(0xffffffffu, ok)) break;
                if (++n > SPIN_LIMIT) __trap();
            }
            if (lane == 0) STAMP(8);
            float ax = 0.f, ay = 0.f;
#pragma unroll
            for (int i = 0; i < 8; i++) { ax += __uint_as_float(vx[i]); ay += __uint_as_float(vy[i]); }
#pragma unroll
            for (int o = 4; o <= 16; o <<= 1) {
                ax += __shfl_xor_sync(0xffffffffu, ax, o);
                ay += __shfl_xor_sync(0xffffffffu, ay, o);
            }
            if (lane < 4) reinterpret_cast<uint32_t*>(p.out)[cta * 4 + lane] = pack_bf16(ax, ay);
        }
    }
}

typedef CUresult (*EncodeFn)(CUtensorMap*, CUtensorMapDataType, cuuint32_t, void*, const cuuint64_t*, const cuuint64_t*,
                             const cuuint32_t*, const cuuint32_t*, CUtensorMapInterleave, CUtensorMapSwizzle,
                             CUtensorMapL2promotion, CUtensorMapFloatOOBfill);

void encode_kv(EncodeFn enc, CUtensorMap* m, const void* ptr) {
    cuuint64_t gd[3] = {64, 8ull * 65536ull, 4};
    cuuint64_t gs[2] = {512, 128};
    cuuint32_t box[3] = {64, 16, 4};
    cuuint32_t es[3] = {1, 1, 1};
    enc(m, CU_TENSOR_MAP_DATA_TYPE_BFLOAT16, 3, const_cast<void*>(ptr), gd, gs, box, es, CU_TENSOR_MAP_INTERLEAVE_NONE,
        CU_TENSOR_MAP_SWIZZLE_128B, CU_TENSOR_MAP_L2_PROMOTION_L2_256B, CU_TENSOR_MAP_FLOAT_OOB_FILL_NONE);
}

}

#define NSTAGES 12

extern "C" void kernel_launch(void* const* d_in, const int* in_sizes, int n_in, void* d_out, int out_size) {
    (void)in_sizes; (void)n_in; (void)out_size;
    static EncodeFn enc = nullptr;
    static int sms = 0;
    if (!enc) {
        cudaDriverEntryPointQueryResult qr;
        void* fn = nullptr;
        cudaGetDriverEntryPoint("cuTensorMapEncodeTiled", &fn, cudaEnableDefault, &qr);
        enc = (EncodeFn)fn;
        int dev = 0;
        cudaGetDevice(&dev);
        cudaDeviceGetAttribute(&sms, cudaDevAttrMultiProcessorCount, dev);
        cudaFuncSetAttribute(fused_decode_kernel<NSTAGES>, cudaFuncAttributeMaxDynamicSharedMemorySize, Smem<NSTAGES>::SIZE);
        cudaFuncSetAttribute(fused_decode_kernel<4>, cudaFuncAttributeMaxDynamicSharedMemorySize, Smem<4>::SIZE);
    }
    Params p;
    for (int b = 0; b < 2; b++) {
        p.x[b] = (const __nv_bfloat16*)d_in[5 * b + 0];
        encode_kv(enc, &p.km[b], d_in[5 * b + 1]);
        encode_kv(enc, &p.vm[b], d_in[5 * b + 2]);
        p.wq[b] = (const __nv_bfloat16*)d_in[5 * b + 3];
        p.wo[b] = (const __nv_bfloat16*)d_in[5 * b + 4];
    }
    p.out = (__nv_bfloat16*)d_out;
    if (sms >= G)
        fused_decode_kernel<NSTAGES><<<G, NTHREADS, Smem<NSTAGES>::SIZE>>>(p);
    else
        fused_decode_kernel<4><<<G, NTHREADS, Smem<4>::SIZE>>>(p);
}
```

```cpp
#include <cuda_runtime.h>
#include <cuda_bf16.h>
#include <cuda.h>
#include <stdint.h>

namespace {

constexpr int G = 132;
constexpr int W = 4;
constexpr int NTHREADS = (W + 2) * 32;
constexpr int TILE_BYTES = 8192;
constexpr int STAGE_BYTES = 2 * TILE_BYTES;
constexpr int TOTAL = 65536;
constexpr int DM = 448;
constexpr int SEG_BYTES = 8 * DM * 2;
constexpr int SLOT_STRIDE = 320;
constexpr int PROG_END = 1 << 30;
constexpr int NS = 12;
constexpr int K0 = 2;
constexpr int Q_DELAY = 1500;
constexpr int MERGE_DELAY = 2500;
constexpr unsigned SPIN_LIMIT = 1u << 22;

struct Params {
    const __nv_bfloat16* x[2];
    const __nv_bfloat16* wo[2];
    __nv_bfloat16* out;
    CUtensorMap km[2];
    CUtensorMap vm[2];
    CUtensorMap wqm[2];
};

typedef unsigned long long u64;

__device__ unsigned int g_epoch;
__device__ unsigned int g_ticket;
__device__ ulonglong2 g_q[16 * 2 * 16 * 4];
__device__ uint4 g_po[16 * 32 * G * 4];
__device__ ulonglong2 g_pml[16 * G * 2 * 2];
__device__ uint4 g_ol[2 * 56 * 64 * 2];

#define STAMP(i)

__device__ __forceinline__ uint32_t smem_u32(const void* p) { return (uint32_t)__cvta_generic_to_shared(p); }
__device__ __forceinline__ void mbar_init(uint32_t bar, uint32_t cnt) {
    asm volatile("mbarrier.init.shared::cta.b64 [%0], %1;" ::"r"(bar), "r"(cnt) : "memory");
}
__device__ __forceinline__ void mbar_expect_tx(uint32_t bar, uint32_t bytes) {
    asm volatile("mbarrier.arrive.expect_tx.shared::cta.b64 _, [%0], %1;" ::"r"(bar), "r"(bytes) : "memory");
}
__device__ __forceinline__ void mbar_arrive(uint32_t bar) {
    asm volatile("mbarrier.arrive.shared::cta.b64 _, [%0];" ::"r"(bar) : "memory");
}
__device__ __forceinline__ bool mbar_try(uint32_t bar, uint32_t parity) {
    uint32_t ok;
    asm volatile("{\n.reg .pred p;\nmbarrier.try_wait.parity.shared::cta.b64 p, [%1], %2;\nselp.u32 %0, 1, 0, p;\n}"
                 : "=r"(ok) : "r"(bar), "r"(parity) : "memory");
    return ok != 0;
}
__device__ __forceinline__ void mbar_wait(uint32_t bar, uint32_t parity) {
    unsigned n = 0;
    while (!mbar_try(bar, parity)) {
        if (++n > SPIN_LIMIT) __trap();
    }
}
__device__ __forceinline__ void tma3d(uint32_t dst, const CUtensorMap* m, int row, uint32_t bar, uint64_t pol) {
    asm volatile(
        "cp.async.bulk.tensor.3d.shared::cluster.global.mbarrier::complete_tx::bytes.L2::cache_hint "
        "[%0], [%1, {%3, %4, %3}], [%2], %5;" ::"r"(dst), "l"(m), "r"(bar), "r"(0), "r"(row), "l"(pol)
        : "memory");
}
__device__ __forceinline__ void bulk_load(uint32_t dst, const void* src, uint32_t bytes, uint32_t bar, uint64_t pol) {
    asm volatile(
        "cp.async.bulk.shared::cluster.global.mbarrier::complete_tx::bytes.L2::cache_hint [%0], [%1], %2, [%3], %4;"
        ::"r"(dst), "l"(src), "r"(bytes), "r"(bar), "l"(pol) : "memory");
}
__device__ __forceinline__ uint64_t evict_first_policy() {
    uint64_t pol;
    asm volatile("createpolicy.fractional.L2::evict_first.b64 %0, 1.0;" : "=l"(pol));
    return pol;
}
__device__ __forceinline__ void ldsm4(uint32_t (&r)[4], uint32_t addr) {
    asm volatile("ldmatrix.sync.aligned.m8n8.x4.shared.b16 {%0,%1,%2,%3}, [%4];"
                 : "=r"(r[0]), "=r"(r[1]), "=r"(r[2]), "=r"(r[3]) : "r"(addr) : "memory");
}
__device__ __forceinline__ void ldsm4t(uint32_t (&r)[4], uint32_t addr) {
    asm volatile("ldmatrix.sync.aligned.m8n8.x4.trans.shared.b16 {%0,%1,%2,%3}, [%4];"
                 : "=r"(r[0]), "=r"(r[1]), "=r"(r[2]), "=r"(r[3]) : "r"(addr) : "memory");
}
__device__ __forceinline__ void mma16816(float (&c)[4], const uint32_t (&a)[4], uint32_t b0, uint32_t b1) {
    asm volatile("mma.sync.aligned.m16n8k16.row.col.f32.bf16.bf16.f32 {%0,%1,%2,%3}, {%4,%5,%6,%7}, {%8,%9}, {%0,%1,%2,%3};"
                 : "+f"(c[0]), "+f"(c[1]), "+f"(c[2]), "+f"(c[3])
                 : "r"(a[0]), "r"(a[1]), "r"(a[2]), "r"(a[3]), "r"(b0), "r"(b1));
}
__device__ __forceinline__ uint32_t movtrans(uint32_t a) {
    uint32_t d;
    asm volatile("movmatrix.sync.aligned.m8n8.trans.b16 %0, %1;" : "=r"(d) : "r"(a));
    return d;
}
__device__ __forceinline__ float ex2(float x) {
    float y;
    asm("ex2.approx.ftz.f32 %0, %1;" : "=f"(y) : "f"(x));
    return y;
}
__device__ __forceinline__ uint32_t pack_bf16(float lo, float hi) {
    uint32_t d;
    asm("cvt.rn.bf16x2.f32 %0, %1, %2;" : "=r"(d) : "f"(hi), "f"(lo));
    return d;
}
__device__ __forceinline__ float bf_lo(uint32_t v) { return __uint_as_float(v << 16); }
__device__ __forceinline__ float bf_hi(uint32_t v) { return __uint_as_float(v & 0xffff0000u); }
__device__ __forceinline__ float warp_max(float v) {
    int k = __float_as_int(v);
    k ^= (k >> 31) & 0x7fffffff;
    k = __reduce_max_sync(0xffffffffu, k);
    k ^= (k >> 31) & 0x7fffffff;
    return __int_as_float(k);
}

__device__ __forceinline__ u64 ll_word(uint32_t v, uint32_t tag) { return ((u64)tag << 32) | v; }
__device__ __forceinline__ void ll_store(ulonglong2* p, uint32_t a, uint32_t b, uint32_t tag) {
    asm volatile("st.relaxed.gpu.global.v2.b64 [%0], {%1, %2};" ::"l"(p), "l"(ll_word(a, tag)), "l"(ll_word(b, tag)) : "memory");
}
__device__ __forceinline__ bool ll_ok(u64 x, u64 y, uint32_t tag) {
    return ((uint32_t)(x >> 32) == tag) & ((uint32_t)(y >> 32) == tag);
}
__device__ __forceinline__ uint32_t pt_enc(float v, uint32_t bit) { return (__float_as_uint(v) & ~1u) | bit; }
__device__ __forceinline__ uint32_t pt_bad(const uint4& v, uint32_t bitmask) {
    return ((v.x ^ bitmask) | (v.y ^ bitmask)) | ((v.z ^ bitmask) | (v.w ^ bitmask));
}
__device__ __forceinline__ void st128(uint4* p, uint32_t a, uint32_t b, uint32_t c, uint32_t d) {
    asm volatile("st.relaxed.gpu.global.v4.b32 [%0], {%1, %2, %3, %4};" ::"l"(p), "r"(a), "r"(b), "r"(c), "r"(d) : "memory");
}
__device__ __forceinline__ void st64(void* p, uint32_t a, uint32_t b) {
    asm volatile("st.relaxed.gpu.global.v2.b32 [%0], {%1, %2};" ::"l"(p), "r"(a), "r"(b) : "memory");
}
__device__ __forceinline__ void ld128(uint4& v, const uint4* p) {
    asm volatile("ld.relaxed.gpu.global.v4.b32 {%0, %1, %2, %3}, [%4];" : "=r"(v.x), "=r"(v.y), "=r"(v.z), "=r"(v.w) : "l"(p) : "memory");
}
__device__ __forceinline__ void ld128_if(uint4& v, const uint4* p, uint32_t bad) {
    asm volatile("{\n.reg .pred p;\n.reg .b32 t;\nand.b32 t, %5, 1;\nsetp.ne.u32 p, t, 0;\n"
                 "@p ld.relaxed.gpu.global.v4.b32 {%0, %1, %2, %3}, [%4];\n}"
                 : "+r"(v.x), "+r"(v.y), "+r"(v.z), "+r"(v.w) : "l"(p), "r"(bad) : "memory");
}
__device__ __forceinline__ void ldu64(u64& v, const void* p) {
    asm volatile("ld.relaxed.gpu.global.b64 %0, [%1];" : "=l"(v) : "l"(p) : "memory");
}
__device__ __forceinline__ void ldu64_if(u64& v, const void* p, uint32_t bad) {
    asm volatile("{\n.reg .pred p;\n.reg .b32 t;\nand.b32 t, %2, 1;\nsetp.ne.u32 p, t, 0;\n"
                 "@p ld.relaxed.gpu.global.b64 %0, [%1];\n}" : "+l"(v) : "l"(p), "r"(bad) : "memory");
}
__device__ __forceinline__ void mma1688(float (&c)[4], uint32_t a0, uint32_t a1, uint32_t b0) {
    asm volatile("mma.sync.aligned.m16n8k8.row.col.f32.bf16.bf16.f32 {%0,%1,%2,%3}, {%4,%5}, {%6}, {%0,%1,%2,%3};"
                 : "+f"(c[0]), "+f"(c[1]), "+f"(c[2]), "+f"(c[3]) : "r"(a0), "r"(a1), "r"(b0));
}
__device__ __forceinline__ bool ll_load(const ulonglong2* p, uint32_t& a, uint32_t& b, uint32_t tag) {
    u64 x, y;
    asm volatile("ld.relaxed.gpu.global.v2.b64 {%0, %1}, [%2];" : "=l"(x), "=l"(y) : "l"(p) : "memory");
    a = (uint32_t)x;
    b = (uint32_t)y;
    return ll_ok(x, y, tag);
}

struct L {
    static constexpr int RING = 0;
    static constexpr int SLOTS = NS * STAGE_BYTES;
    static constexpr int SLOTML = SLOTS + W * 2 * SLOT_STRIDE * 4;
    static constexpr int RED = SLOTML + W * 16;
    static constexpr int OFIN = RED + W * DM * 4;
    static constexpr int Q0 = OFIN + 64 * 4;
    static constexpr int TK = Q0 + 16 * 128 * 8;
    static constexpr int BARS = TK + 32 * 4;
    static constexpr int NBARS = 3 * NS + 7 + 8;
    static constexpr int SIZE = BARS + NBARS * 8;
};

__global__ void __launch_bounds__(NTHREADS, 1) fused_decode_kernel(const __grid_constant__ Params p) {
    extern __shared__ __align__(1024) unsigned char smem_raw[];
    static_assert(NS % W == 0 && K0 >= 1 && K0 <= NS - 4 && W == 4, "geometry");
    unsigned char* smem = smem_raw;
    const uint32_t sbase = smem_u32(smem);
    const int warp = threadIdx.x >> 5, lane = threadIdx.x & 31;
    const int cta = blockIdx.x;
    const bool has_task = cta < 128;
    const bool isX = has_task && cta >= 64, isY = cta < 64;
    const int slice = cta & 63;

    const uint32_t bar_full = sbase + L::BARS;
    const uint32_t bar_fullv = bar_full + NS * 8;
    const uint32_t bar_empty = bar_fullv + NS * 8;
    const uint32_t bar_ofin = bar_empty + NS * 8;
    const uint32_t bar_q = bar_ofin + 8;
    const uint32_t bar_q2 = bar_q + 8;
    const uint32_t bar_q3 = bar_q2 + 8;
    const uint32_t bar_wq = bar_q3 + 8;
    const uint32_t bar_wo = bar_wq + 8;
    const uint32_t bar_red = bar_wo + 64;
    const uint32_t bar_wqdone = bar_red + 8;
    volatile int* s_tk = reinterpret_cast<volatile int*>(smem + L::TK);
    float* s_slots = reinterpret_cast<float*>(smem + L::SLOTS);
    float* s_slotml = reinterpret_cast<float*>(smem + L::SLOTML);
    float* s_red = reinterpret_cast<float*>(smem + L::RED);
    float* s_ofin = reinterpret_cast<float*>(smem + L::OFIN);
    uint2* s_q0 = reinterpret_cast<uint2*>(smem + L::Q0);

    uint64_t pol = 0;
    auto issue = [&](int s, int t) {
        s_tk[s] = t;
        s_tk[30] = t;
        const uint32_t dst = sbase + L::RING + s * STAGE_BYTES;
        const int b = t >> 15, row = (t & 32767) << 4;
        mbar_expect_tx(bar_full + s * 8, TILE_BYTES);
        tma3d(dst, &p.km[b], row, bar_full + s * 8, pol);
        mbar_expect_tx(bar_fullv + s * 8, TILE_BYTES);
        tma3d(dst + TILE_BYTES, &p.vm[b], row, bar_fullv + s * 8, pol);
    };
    if (threadIdx.x == W * 32) {
        STAMP(0);
        mbar_init(bar_wq, 1);
#pragma unroll
        for (int i = 0; i < K0; i++) { mbar_init(bar_full + i * 8, 1); mbar_init(bar_fullv + i * 8, 1); }
        asm volatile("fence.mbarrier_init.release.cluster;" ::: "memory");
        pol = evict_first_policy();
        if (has_task) {
            mbar_expect_tx(bar_wq, 448 * 128);
#pragma unroll
            for (int i = 0; i < 2; i++)
                asm volatile(
                    "cp.async.bulk.tensor.2d.shared::cluster.global.mbarrier::complete_tx::bytes.L2::cache_hint "
                    "[%0], [%1, {%3, %4}], [%2], %5;" ::"r"(sbase + L::RING + (NS - 4) * STAGE_BYTES + i * 224 * 128),
                    "l"(&p.wqm[cta >> 6]), "r"(bar_wq), "r"((cta & 63) * 64), "r"(i * 224), "l"(pol) : "memory");
        }
#pragma unroll
        for (int i = 0; i < K0; i++) issue(i, cta + G * i);
#pragma unroll
        for (int i = 0; i < L::NBARS; i++)
            if (!(i < K0 || (i >= NS && i < NS + K0) || i == 3 * NS + 4)) mbar_init(bar_full + i * 8, i >= L::NBARS - 2 ? W : 1);
        asm volatile("fence.mbarrier_init.release.cluster;" ::: "memory");
    }

    if (warp == W) {
        __syncwarp();
        asm volatile("bar.arrive 2, %0;" ::"n"(NTHREADS) : "memory");
        if (lane == 0) {
            STAMP(1);
            asm volatile("prefetch.tensormap [%0];" ::"l"(&p.km[1]) : "memory");
            asm volatile("prefetch.tensormap [%0];" ::"l"(&p.vm[1]) : "memory");
            int s = K0;
            uint32_t ph = 1;
            bool first_lap = has_task;
            while (true) {
                mbar_wait(bar_empty + s * 8, ph);
                if (first_lap && s == NS - 4) { mbar_wait(bar_wqdone, 0); first_lap = false; }
                const int t = (int)atomicAdd(&g_ticket, 1u) + G * K0;
                if (t >= TOTAL) break;
                issue(s, t);
                if (++s == NS) { s = 0; ph ^= 1; }
            }
            STAMP(2);
            s_tk[30] = PROG_END;
            s_tk[31] = s;
            const int s0 = s;
#pragma unroll 1
            for (int j = 0; j < W; j++) {
                if (j > 0) mbar_wait(bar_empty + s * 8, ph);
                s_tk[s] = TOTAL;
                mbar_arrive(bar_full + s * 8);
                if (++s == NS) { s = 0; ph ^= 1; }
            }
            if (isY) {
                mbar_wait(bar_wqdone, 0);
                STAMP(9);
                int ws = s0;
#pragma unroll 1
                for (int k = 0; k < 8; k++) {
                    const char* src = reinterpret_cast<const char*>(p.wo[0]) + (size_t)(k * 64 + slice) * SEG_BYTES;
                    mbar_expect_tx(bar_wo + k * 8, SEG_BYTES);
                    bulk_load(sbase + L::RING + ws * STAGE_BYTES + (k & 1) * SEG_BYTES, src, SEG_BYTES, bar_wo + k * 8, pol);
                    if (k & 1) { if (++ws == NS) ws = 0; }
                }
            }
        }
    } else if (warp == W + 1) {
        uint32_t tag;
        asm volatile("ld.relaxed.gpu.global.u32 %0, [%1];" : "=r"(tag) : "l"(&g_epoch) : "memory");
        tag += 1;
        auto wait_progress = [&](int target) {
            unsigned n = 0;
            while (s_tk[30] < target) {
                __nanosleep(100);
                if (++n > SPIN_LIMIT) __trap();
            }
        };
        {
            bool synced = false;
#pragma unroll 1
            for (int h = 0; h < 16; h++) {
                if (h == 1) wait_progress(Q_DELAY);
                unsigned n = 0;
                uint32_t qa[4], qb[4];
                while (true) {
                    bool ok = true;
#pragma unroll
                    for (int i = 0; i < 4; i++) ok &= ll_load(g_q + h * 128 + i * 32 + lane, qa[i], qb[i], tag);
                    if (!synced) {
                        asm volatile("bar.sync 2, %0;" ::"n"(NTHREADS) : "memory");
                        if (has_task) mbar_wait(bar_wqdone, 0);
                        synced = true;
                    }
                    if (__all_sync(0xffffffffu, ok)) break;
                    if (++n > SPIN_LIMIT) __trap();
                }
#pragma unroll
                for (int i = 0; i < 4; i++) s_q0[h * 128 + i * 32 + lane] = make_uint2(qa[i], qb[i]);
                __syncwarp();
                if (lane == 0) {
                    if (h == 0) mbar_arrive(bar_q);
                    if (h == 3) mbar_arrive(bar_q2);
                    if (h == 15) mbar_arrive(bar_q3);
                }
            }
        }
        if (has_task) {
            const uint32_t bit = tag & 1u, bitmask = 0u - bit;
            const int qh = slice >> 5;
            const int g = lane >> 2, t4 = lane & 3;
            pol = evict_first_policy();
            float y[7][4];
#pragma unroll
            for (int j = 0; j < 7; j++) { y[j][0] = 0.f; y[j][1] = 0.f; y[j][2] = 0.f; y[j][3] = 0.f; }
#pragma unroll 1
            for (int h = isX ? 8 : 0; h < 16; h = (h == 7) ? 14 : h + 1) {
                if (isX || h < 8) {
                    uint32_t wf[14][4];
                    if (isX) {
                        wait_progress(h * 4096);
                        if (lane == 0) {
                            asm volatile("fence.proxy.async.shared::cta;" ::: "memory");
                            mbar_expect_tx(bar_wo + (h & 7) * 8, SEG_BYTES);
                            bulk_load(sbase + L::RED,
                                      reinterpret_cast<const char*>(p.wo[1]) + (size_t)((h & 7) * 64 + slice) * SEG_BYTES,
                                      SEG_BYTES, bar_wo + (h & 7) * 8, pol);
                        }
                        mbar_wait(bar_wo + (h & 7) * 8, 0);
                        const int r = lane & 7, row = 4 * ((r >> 1) & 1) + 2 * (r >> 2) + (r & 1);
                        const uint32_t wa = sbase + L::RED + row * (DM * 2) + (lane >> 3) * 16;
#pragma unroll
                        for (int x = 0; x < 14; x++) ldsm4t(wf[x], wa + x * 64);
                        __syncwarp();
                    }
                    wait_progress(h < 15 ? (h + 1) * 4096 + MERGE_DELAY : PROG_END);
                    u64 ml[5];
                    uint4 ov[9];
                    const ulonglong2* pml = g_pml + ((h * G + lane) * 2 + qh) * 2;
                    const uint4* pr = g_po + ((size_t)(h * 32 + (slice >> 1)) * G + (lane >> 1)) * 4 + (slice & 1) * 2 + (lane & 1);
                    constexpr int PRS = 16 * 4;
                    const ulonglong2* pml4 = pml + (lane < G - 128 ? 4 * 128 : 0);
                    const uint4* pr8 = pr + (lane < (G - 128) * 2 ? 8 * PRS : 0);
#pragma unroll
                    for (int j = 0; j < 5; j++) ldu64(ml[j], j < 4 ? pml + j * 128 : pml4);
#pragma unroll
                    for (int it = 0; it < 9; it++) ld128(ov[it], it < 8 ? pr + it * PRS : pr8);
                    unsigned n = 0;
                    while (true) {
                        uint32_t bm[5], bo[9], bad = 0;
#pragma unroll
                        for (int j = 0; j < 5; j++) { bm[j] = (uint32_t)(ml[j] >> 32) ^ bitmask; bad |= bm[j]; }
#pragma unroll
                        for (int it = 0; it < 9; it++) { bo[it] = pt_bad(ov[it], bitmask); bad |= bo[it]; }
                        if (__all_sync(0xffffffffu, (bad & 1u) == 0) && (h == 15 || n > 0)) break;
                        if (h != 15) __nanosleep(400);
                        if (++n > SPIN_LIMIT) __trap();
#pragma unroll
                        for (int j = 0; j < 5; j++) ldu64_if(ml[j], j < 4 ? pml + j * 128 : pml4, bm[j]);
#pragma unroll
                        for (int it = 0; it < 9; it++) ld128_if(ov[it], it < 8 ? pr + it * PRS : pr8, bo[it]);
                    }
                    if (lane == 0) STAMP(32 + h);
                    float mj[5];
#pragma unroll
                    for (int j = 0; j < 5; j++) mj[j] = __uint_as_float((uint32_t)ml[j]);
                    const float M = warp_max(fmaxf(fmaxf(fmaxf(mj[0], mj[1]), fmaxf(mj[2], mj[3])), mj[4]));
                    float wc[5], Ls = 0.f;
#pragma unroll
                    for (int j = 0; j < 5; j++) {
                        wc[j] = ex2(mj[j] - M);
                        if (j == 4 && lane >= G - 128) wc[j] = 0.f;
                        Ls += wc[j] * __uint_as_float((uint32_t)(ml[j] >> 32));
                    }
                    float a0 = 0.f, a1 = 0.f, a2 = 0.f, a3 = 0.f;
#pragma unroll
                    for (int it = 0; it < 9; it++) {
                        const float wv = __shfl_sync(0xffffffffu, wc[it >> 1], 16 * (it & 1) + (lane >> 1));
                        a0 += wv * __uint_as_float(ov[it].x);
                        a1 += wv * __uint_as_float(ov[it].y);
                        a2 += wv * __uint_as_float(ov[it].z);
                        a3 += wv * __uint_as_float(ov[it].w);
                        if (it == 0) Ls += __shfl_xor_sync(0xffffffffu, Ls, 1);
                    }
                    const bool up = lane & 2;
                    float ax = (up ? a2 : a0) + __shfl_xor_sync(0xffffffffu, up ? a0 : a2, 2);
                    float ay = (up ? a3 : a1) + __shfl_xor_sync(0xffffffffu, up ? a1 : a3, 2);
                    Ls += __shfl_xor_sync(0xffffffffu, Ls, 2);
#pragma unroll
                    for (int o = 4; o <= 16; o <<= 1) {
                        ax += __shfl_xor_sync(0xffffffffu, ax, o);
                        ay += __shfl_xor_sync(0xffffffffu, ay, o);
                        Ls += __shfl_xor_sync(0xffffffffu, Ls, o);
                    }
                    const float inv = __fdividef(1.0f, Ls);
                    const uint32_t o2 = pack_bf16(ax * inv, ay * inv);
                    if (isY) {
                        if (lane < 4)
                            *reinterpret_cast<float2*>(s_ofin + h * 8 + 4 * (lane & 1) + (lane & 2)) = make_float2(bf_lo(o2), bf_hi(o2));
                        __syncwarp();
                        if (h == 7 && lane == 0) mbar_arrive(bar_ofin);
                    } else {
                        if (lane == 0) STAMP(3);
#pragma unroll
                        for (int q = 0; q < 4; q++) {
                            const uint32_t bq = (g == 2 * q) ? o2 : 0u;
#pragma unroll
                            for (int j = 0; j < 7; j++) {
                                const int i = 4 * j + q;
                                mma1688(y[j], wf[i >> 1][2 * (i & 1)], wf[i >> 1][2 * (i & 1) + 1], bq);
                            }
                        }
                    }
                }
                if (h >= 14) {
                    const bool real = (h == 15);
                    const uint32_t obit = real ? bit : bit ^ 1u;
                    char* dst = reinterpret_cast<char*>(g_ol + ((size_t)((isX ? 56 : 0) + g) * 64 + slice) * 2) + t4 * 8;
                    if (isX) {
#pragma unroll
                        for (int j = 0; j < 7; j++) st64(dst + (size_t)j * 8 * 64 * 32, pt_enc(y[j][0], obit), pt_enc(y[j][2], obit));
                        if (lane == 0) STAMP(4);
                    } else {
                        if (real) mbar_wait(bar_red, 0); else wait_progress(14 * 4096);
                        if (lane == 0) STAMP(5);
#pragma unroll
                        for (int j = 0; j < 7; j++) {
                            float vx = 0.f, vy = 0.f;
#pragma unroll
                            for (int w = 0; w < W; w++) {
                                const float2 v = *reinterpret_cast<const float2*>(s_red + w * DM + 64 * j + 2 * lane);
                                vx += v.x;
                                vy += v.y;
                            }
                            st64(dst + (size_t)j * 8 * 64 * 32, pt_enc(vx, obit), pt_enc(vy, obit));
                        }
                        if (lane == 0) STAMP(11);
                    }
                }
            }
            if (cta == 127 && lane == 0) {
                asm volatile("st.relaxed.gpu.global.u32 [%0], %1;" ::"l"(&g_ticket), "r"(0u) : "memory");
                asm volatile("st.relaxed.gpu.global.u32 [%0], %1;" ::"l"(&g_epoch), "r"(tag) : "memory");
            }
        }
    } else {
        uint32_t tag;
        asm volatile("ld.relaxed.gpu.global.u32 %0, [%1];" : "=r"(tag) : "l"(&g_epoch) : "memory");
        const int g = lane >> 2, t4 = lane & 3;
        if (has_task) {
            const int tb = cta >> 6, qs = cta & 63;
            const int r = threadIdx.x >> 3, c8 = threadIdx.x & 7;
            const uint2* xp = reinterpret_cast<const uint2*>(p.x[tb] + 28 * r);
            uint2 xv[7];
#pragma unroll
            for (int i = 0; i < 7; i++)
                asm volatile("ld.global.nc.v2.u32 {%0,%1}, [%2];" : "=r"(xv[i].x), "=r"(xv[i].y) : "l"(xp + i));
            asm volatile("bar.sync 2, %0;" ::"n"(NTHREADS) : "memory");
            mbar_wait(bar_wq, 0);
            const uint4* wv = reinterpret_cast<const uint4*>(smem + L::RING + (NS - 4) * STAGE_BYTES) + 28 * r * 8 + c8;
            float acc[8];
#pragma unroll
            for (int j = 0; j < 8; j++) acc[j] = 0.f;
#pragma unroll
            for (int i = 0; i < 28; i++) {
                const uint32_t xw = (i & 2) ? xv[i >> 2].y : xv[i >> 2].x;
                const float xs = (i & 1) ? bf_hi(xw) : bf_lo(xw);
                const uint4 v = wv[i * 8];
                acc[0] += xs * bf_lo(v.x); acc[1] += xs * bf_hi(v.x);
                acc[2] += xs * bf_lo(v.y); acc[3] += xs * bf_hi(v.y);
                acc[4] += xs * bf_lo(v.z); acc[5] += xs * bf_hi(v.z);
                acc[6] += xs * bf_lo(v.w); acc[7] += xs * bf_hi(v.w);
            }
#pragma unroll
            for (int j = 0; j < 8; j++) {
                acc[j] += __shfl_xor_sync(0xffffffffu, acc[j], 8);
                acc[j] += __shfl_xor_sync(0xffffffffu, acc[j], 16);
            }
            if (lane < 8) {
                float4* d = reinterpret_cast<float4*>(s_red + warp * 64 + lane * 8);
                d[0] = make_float4(acc[0], acc[1], acc[2], acc[3]);
                d[1] = make_float4(acc[4], acc[5], acc[6], acc[7]);
            }
            asm volatile("bar.sync 1, %0;" ::"n"(W * 32) : "memory");
            if (threadIdx.x < 16) {
                const int il = threadIdx.x >> 2;
                float q[4];
#pragma unroll
                for (int k = 0; k < 4; k++) {
                    const int d = 16 * il + 2 * t4 + (k & 1) + 8 * (k >> 1);
                    q[k] = 0.f;
#pragma unroll
                    for (int w = 0; w < W; w++) q[k] += s_red[w * 64 + d];
                }
                ll_store(g_q + ((tb * 16 + (qs >> 2)) * 16 + (qs & 3) * 4 + il) * 4 + t4,
                         pack_bf16(q[0], q[1]), pack_bf16(q[2], q[3]), tag + 1);
            }
            __syncwarp();
            if (lane == 0) mbar_arrive(bar_wqdone);
            if (threadIdx.x == 0) STAMP(6);
        } else {
            asm volatile("bar.sync 2, %0;" ::"n"(NTHREADS) : "memory");
        }
        tag += 1;
        const uint32_t bit = tag & 1u;

        float acc[4][4];
#pragma unroll
        for (int i = 0; i < 4; i++) { acc[i][0] = 0.f; acc[i][1] = 0.f; acc[i][2] = 0.f; acc[i][3] = 0.f; }
        float m0 = -INFINITY, m1 = -INFINITY;
        float lacc[4] = {0.f, 0.f, 0.f, 0.f};
        const uint32_t ones[4] = {0x3f803f80u, 0x3f803f80u, 0x3f803f80u, 0x3f803f80u};
        uint32_t qf[16][2];
        int cur = 0;
        const uint32_t krow = (lane & 7) + 8 * ((lane >> 3) & 1), vrow = (lane & 7) + 8 * (lane >> 4);
        const uint32_t koff = krow * 128 + (((lane >> 4) ^ (krow & 7)) << 4);
        const uint32_t voff = TILE_BYTES + vrow * 128 + ((((lane >> 3) & 1) ^ (vrow & 7)) << 4);
        const float SC = 0.0625f * 1.4426950408889634f;
        int s = warp;
        uint32_t ph = 0;
        mbar_wait(bar_q, 0);
#pragma unroll
        for (int i = 0; i < 16; i++) {
            const uint2 v = s_q0[((g & 1) * 16 + i) * 4 + t4];
            qf[i][0] = v.x;
            qf[i][1] = v.y;
        }
        if (threadIdx.x == 0) STAMP(7);
        while (true) {
            mbar_wait(bar_full + s * 8, ph);
            const int t = s_tk[s];
            const int h = t >> 12;
            if (h != cur) {
                while (cur < h) {
                    float* sl = s_slots + warp * 2 * SLOT_STRIDE + 16 * t4 + 8 * (t4 >> 1) + g;
                    if (lane == 0) *reinterpret_cast<float4*>(s_slotml + warp * 4) = make_float4(m0, lacc[0], m1, lacc[1]);
#pragma unroll
                    for (int j = 0; j < 4; j++) {
                        sl[80 * j] = acc[j][0];
                        sl[80 * j + SLOT_STRIDE] = acc[j][1];
                        sl[80 * j + 8] = acc[j][2];
                        sl[80 * j + 8 + SLOT_STRIDE] = acc[j][3];
                    }
                    uint4* po = g_po + ((size_t)(cur * 32 + 8 * warp + (lane >> 2)) * G + cta) * 4 + (lane & 3);
                    ulonglong2* pml = g_pml + ((cur * G + cta) * 2 + (warp >> 1)) * 2 + lane;
                    asm volatile("bar.sync 1, %0;" ::"n"(W * 32) : "memory");
                    if (threadIdx.x == 0) STAMP(16 + cur);
                    float2 mlw[W];
                    float4 sv[W];
                    float M = -INFINITY;
#pragma unroll
                    for (int w = 0; w < W; w++) {
                        mlw[w] = *reinterpret_cast<const float2*>(s_slotml + w * 4 + (warp & 2));
                        sv[w] = *reinterpret_cast<const float4*>(s_slots + (w * 2 + (warp >> 1)) * SLOT_STRIDE + 160 * (warp & 1) + 4 * lane + (lane & 24));
                        M = fmaxf(M, mlw[w].x);
                    }
                    const float R = (M == -INFINITY) ? 0.f : M;
                    float4 o = make_float4(0.f, 0.f, 0.f, 0.f);
                    float Lw = 0.f;
#pragma unroll
                    for (int w = 0; w < W; w++) {
                        const float f = ex2(mlw[w].x - R);
                        Lw += f * mlw[w].y;
                        o.x += f * sv[w].x; o.y += f * sv[w].y; o.z += f * sv[w].z; o.w += f * sv[w].w;
                    }
                    st128(po, pt_enc(o.x, bit), pt_enc(o.y, bit), pt_enc(o.z, bit), pt_enc(o.w, bit));
                    const bool mlwriter = !(warp & 1) && lane < 2;
                    if (mlwriter) ll_store(pml, __float_as_uint(M), __float_as_uint(M), pt_enc(Lw, bit));
                    if (cur == 15 && threadIdx.x == 0) STAMP(13);
                    if (cur == 13) {
                        st128(po + 2 * 32 * G * 4, bit ^ 1u, bit ^ 1u, bit ^ 1u, bit ^ 1u);
                        if (mlwriter) ll_store(pml + 2 * G * 4, 0u, 0u, bit ^ 1u);
                    }
#pragma unroll
                    for (int i = 0; i < 4; i++) { acc[i][0] = 0.f; acc[i][1] = 0.f; acc[i][2] = 0.f; acc[i][3] = 0.f; }
                    m0 = -INFINITY; m1 = -INFINITY;
                    lacc[0] = 0.f; lacc[1] = 0.f; lacc[2] = 0.f; lacc[3] = 0.f;
                    cur++;
                    asm volatile("bar.sync 1, %0;" ::"n"(W * 32) : "memory");
                }
                if (h >= 16) break;
                mbar_wait(h > 3 ? bar_q3 : bar_q2, 0);
#pragma unroll
                for (int i = 0; i < 16; i++) {
                    const uint2 v = s_q0[h * 128 + ((g & 1) * 16 + i) * 4 + t4];
                    qf[i][0] = v.x;
                    qf[i][1] = v.y;
                }
            }
            const uint32_t stage = sbase + L::RING + s * STAGE_BYTES;
            float sc[4][4];
#pragma unroll
            for (int c = 0; c < 4; c++) { sc[c][0] = 0.f; sc[c][1] = 0.f; sc[c][2] = 0.f; sc[c][3] = 0.f; }
            const uint32_t kb = stage + koff;
#pragma unroll
            for (int i = 0; i < 16; i++) {
                uint32_t a[4];
                ldsm4(a, (kb ^ ((i & 3) << 5)) + (i >> 2) * 2048);
                mma16816(sc[i & 3], a, qf[i][0], qf[i][1]);
            }
            const float s0 = ((sc[0][0] + sc[1][0]) + (sc[2][0] + sc[3][0])) * SC;
            const float s1 = ((sc[0][1] + sc[1][1]) + (sc[2][1] + sc[3][1])) * SC;
            const float s2 = ((sc[0][2] + sc[1][2]) + (sc[2][2] + sc[3][2])) * SC;
            const float s3 = ((sc[0][3] + sc[1][3]) + (sc[2][3] + sc[3][3])) * SC;
            float n0 = fmaxf(s0, s2), n1 = fmaxf(s1, s3);
            if (__any_sync(0xffffffffu, (n0 > m0) | (n1 > m1))) {
                n0 = fmaxf(warp_max(n0), m0);
                n1 = fmaxf(warp_max(n1), m1);
                const float f0 = ex2(m0 - n0), f1 = ex2(m1 - n1);
                m0 = n0; m1 = n1;
                lacc[0] *= f0; lacc[1] *= f1; lacc[2] *= f0; lacc[3] *= f1;
#pragma unroll
                for (int i = 0; i < 4; i++) { acc[i][0] *= f0; acc[i][1] *= f1; acc[i][2] *= f0; acc[i][3] *= f1; }
            }
            const float p0 = ex2(s0 - m0), p1 = ex2(s1 - m1), p2 = ex2(s2 - m0), p3 = ex2(s3 - m1);
            const uint32_t b0 = movtrans(pack_bf16(p0, p1));
            const uint32_t b1 = movtrans(pack_bf16(p2, p3));
            mma16816(lacc, ones, b0, b1);
            mbar_wait(bar_fullv + s * 8, ph);
            const uint32_t vb = stage + voff;
#pragma unroll
            for (int q = 0; q < 4; q++) {
                const uint32_t c0 = ((g >> 1) == q) ? b0 : 0u, c1 = ((g >> 1) == q) ? b1 : 0u;
#pragma unroll
                for (int j = 0; j < 4; j++) {
                    uint32_t a[4];
                    ldsm4t(a, (vb ^ (q << 5)) + j * 2048);
                    mma16816(acc[j], a, c0, c1);
                }
            }
            __syncwarp();
            if (lane == 0) mbar_arrive(bar_empty + s * 8);
            s += W;
            if (s >= NS) { s -= NS; ph ^= 1; }
        }

        if (isY) {
            mbar_wait(bar_ofin, 0);
            const int ws0 = s_tk[31];
            float a[7][2];
#pragma unroll
            for (int j = 0; j < 7; j++) { a[j][0] = 0.f; a[j][1] = 0.f; }
#pragma unroll 1
            for (int k = warp; k < 8; k += W) {
                int ws = ws0 + (k >> 1);
                if (ws >= NS) ws -= NS;
                const uint32_t* wseg =
                    reinterpret_cast<const uint32_t*>(smem + L::RING + ws * STAGE_BYTES + (k & 1) * SEG_BYTES);
                mbar_wait(bar_wo + k * 8, 0);
#pragma unroll
                for (int r = 0; r < 8; r++) {
                    const float o = s_ofin[k * 8 + r];
#pragma unroll
                    for (int j = 0; j < 7; j++) {
                        const uint32_t wv = wseg[r * (DM / 2) + 32 * j + lane];
                        a[j][0] += o * bf_lo(wv);
                        a[j][1] += o * bf_hi(wv);
                    }
                }
            }
#pragma unroll
            for (int j = 0; j < 7; j++)
                *reinterpret_cast<float2*>(s_red + warp * DM + 64 * j + 2 * lane) = make_float2(a[j][0], a[j][1]);
            __syncwarp();
            if (lane == 0) mbar_arrive(bar_red);
        }
        if (isX && slice < 56 && !(warp & 1)) {
            const bool fb = warp < 2;
            const uint32_t bitmask = 0u - bit;
            const uint4* src = g_ol + (size_t)((fb ? 56 : 0) + slice) * 64 * 2 + lane;
            const int et = 2 * (lane & 1) + ((lane >> 1) & 1), es = (lane >> 2) & 1;
            const int col = fb ? DM + 64 * (slice >> 3) + 16 * et + 8 * es + (slice & 7) : 8 * slice + 2 * et + es;
            __nv_bfloat16* dst = p.out + col;
            unsigned n = 0;
            while (true) {
                uint4 v[4];
#pragma unroll
                for (int i = 0; i < 4; i++) ld128(v[i], src + i * 32);
                const uint32_t bad = (pt_bad(v[0], bitmask) | pt_bad(v[1], bitmask)) | (pt_bad(v[2], bitmask) | pt_bad(v[3], bitmask));
                const bool done = __all_sync(0xffffffffu, (bad & 1u) == 0);
                const float a0 = (__uint_as_float(v[0].x) + __uint_as_float(v[1].x)) + (__uint_as_float(v[2].x) + __uint_as_float(v[3].x));
                const float a1 = (__uint_as_float(v[0].y) + __uint_as_float(v[1].y)) + (__uint_as_float(v[2].y) + __uint_as_float(v[3].y));
                const float a2 = (__uint_as_float(v[0].z) + __uint_as_float(v[1].z)) + (__uint_as_float(v[2].z) + __uint_as_float(v[3].z));
                const float a3 = (__uint_as_float(v[0].w) + __uint_as_float(v[1].w)) + (__uint_as_float(v[2].w) + __uint_as_float(v[3].w));
                if (done || n == 0) {
                    const bool u1 = lane & 2, u2 = lane & 4;
                    const float bx = (u1 ? a2 : a0) + __shfl_xor_sync(0xffffffffu, u1 ? a0 : a2, 2);
                    const float by = (u1 ? a3 : a1) + __shfl_xor_sync(0xffffffffu, u1 ? a1 : a3, 2);
                    float c = (u2 ? by : bx) + __shfl_xor_sync(0xffffffffu, u2 ? bx : by, 4);
                    c += __shfl_xor_sync(0xffffffffu, c, 8);
                    c += __shfl_xor_sync(0xffffffffu, c, 16);
                    if (done && lane < 8) *dst = __float2bfloat16(c);
                    if (done) break;
                }
                if (++n > SPIN_LIMIT) __trap();
            }
            if (lane == 0 && !(warp & 1)) STAMP(fb ? 8 : 12);
        }
    }
}

constexpr int FB_SPLIT = 64;
__device__ float g_fq[2 * 4096];
__device__ float g_fp[16 * FB_SPLIT * 8 * 2 * 264];

__global__ void fb_q_kernel(const __nv_bfloat16* x, const __nv_bfloat16* wq, int b) {
    const int n = blockIdx.x * blockDim.x + threadIdx.x;
    float a = 0.f;
    for (int k = 0; k < DM; k++) a += __bfloat162float(x[k]) * __bfloat162float(wq[(size_t)k * 4096 + n]);
    g_fq[b * 4096 + n] = __bfloat162float(__float2bfloat16(a));
}
__global__ void fb_attn_kernel(const uint4* k, const uint4* v, int b) {
    const int hk = blockIdx.y, warp = threadIdx.x >> 5, lane = threadIdx.x & 31;
    float q[2][8], o[2][8], m[2] = {-INFINITY, -INFINITY}, l[2] = {0.f, 0.f};
    for (int h = 0; h < 2; h++)
        for (int j = 0; j < 8; j++) { q[h][j] = g_fq[b * 4096 + (hk * 2 + h) * 256 + lane * 8 + j]; o[h][j] = 0.f; }
    const int n = 65536 / FB_SPLIT / 8;
    const size_t row0 = (size_t)hk * 65536 + (size_t)(blockIdx.x * 8 + warp) * n;
    for (int i = 0; i < n; i++) {
        const uint4 kk = k[(row0 + i) * 32 + lane], vv = v[(row0 + i) * 32 + lane];
        const float kf[8] = {bf_lo(kk.x), bf_hi(kk.x), bf_lo(kk.y), bf_hi(kk.y), bf_lo(kk.z), bf_hi(kk.z), bf_lo(kk.w), bf_hi(kk.w)};
        const float vf[8] = {bf_lo(vv.x), bf_hi(vv.x), bf_lo(vv.y), bf_hi(vv.y), bf_lo(vv.z), bf_hi(vv.z), bf_lo(vv.w), bf_hi(vv.w)};
#pragma unroll
        for (int h = 0; h < 2; h++) {
            float s = 0.f;
#pragma unroll
            for (int j = 0; j < 8; j++) s += q[h][j] * kf[j];
            for (int d = 16; d >= 1; d >>= 1) s += __shfl_xor_sync(0xffffffffu, s, d);
            s *= 0.0625f * 1.4426950408889634f;
            const float mn = fmaxf(m[h], s), f = ex2(m[h] - mn), pr = ex2(s - mn);
            m[h] = mn;
            l[h] = l[h] * f + pr;
#pragma unroll
            for (int j = 0; j < 8; j++) o[h][j] = o[h][j] * f + pr * vf[j];
        }
    }
    for (int h = 0; h < 2; h++) {
        float* d = g_fp + ((((size_t)(b * 8 + hk) * FB_SPLIT + blockIdx.x) * 8 + warp) * 2 + h) * 264;
        for (int j = 0; j < 8; j++) d[lane * 8 + j] = o[h][j];
        if (lane == 0) { d[256] = m[h]; d[257] = l[h]; }
    }
}
__global__ void fb_merge_kernel() {
    const int hq = blockIdx.x;
    const float* base = g_fp + ((size_t)(hq >> 1) * FB_SPLIT * 8 * 2 + (hq & 1)) * 264;
    float M = -INFINITY, Ls = 0.f, a = 0.f;
    for (int i = 0; i < FB_SPLIT * 8; i++) M = fmaxf(M, base[(size_t)i * 528 + 256]);
    for (int i = 0; i < FB_SPLIT * 8; i++) {
        const float w = ex2(base[(size_t)i * 528 + 256] - M);
        Ls += w * base[(size_t)i * 528 + 257];
        a += w * base[(size_t)i * 528 + threadIdx.x];
    }
    g_fq[hq * 256 + threadIdx.x] = __bfloat162float(__float2bfloat16(a / Ls));
}
__global__ void fb_out_kernel(const __nv_bfloat16* wo, __nv_bfloat16* out, int b) {
    const int n = blockIdx.x * 64 + threadIdx.x;
    float a = 0.f;
    for (int k = 0; k < 4096; k++) a += g_fq[b * 4096 + k] * __bfloat162float(wo[(size_t)k * DM + n]);
    out[b * DM + n] = __float2bfloat16(a);
}

typedef CUresult (*EncodeFn)(CUtensorMap*, CUtensorMapDataType, cuuint32_t, void*, const cuuint64_t*, const cuuint64_t*,
                             const cuuint32_t*, const cuuint32_t*, CUtensorMapInterleave, CUtensorMapSwizzle,
                             CUtensorMapL2promotion, CUtensorMapFloatOOBfill);

void encode_kv(EncodeFn enc, CUtensorMap* m, const void* ptr) {
    cuuint64_t gd[3] = {64, 8ull * 65536ull, 4};
    cuuint64_t gs[2] = {512, 128};
    cuuint32_t box[3] = {64, 16, 4};
    cuuint32_t es[3] = {1, 1, 1};
    enc(m, CU_TENSOR_MAP_DATA_TYPE_BFLOAT16, 3, const_cast<void*>(ptr), gd, gs, box, es, CU_TENSOR_MAP_INTERLEAVE_NONE,
        CU_TENSOR_MAP_SWIZZLE_128B, CU_TENSOR_MAP_L2_PROMOTION_L2_256B, CU_TENSOR_MAP_FLOAT_OOB_FILL_NONE);
}

void encode_wq(EncodeFn enc, CUtensorMap* m, const void* ptr) {
    cuuint64_t gd[2] = {4096, 448};
    cuuint64_t gs[1] = {8192};
    cuuint32_t box[2] = {64, 224};
    cuuint32_t es[2] = {1, 1};
    enc(m, CU_TENSOR_MAP_DATA_TYPE_BFLOAT16, 2, const_cast<void*>(ptr), gd, gs, box, es, CU_TENSOR_MAP_INTERLEAVE_NONE,
        CU_TENSOR_MAP_SWIZZLE_NONE, CU_TENSOR_MAP_L2_PROMOTION_L2_128B, CU_TENSOR_MAP_FLOAT_OOB_FILL_NONE);
}

}

extern "C" void kernel_launch(void* const* d_in, const int* in_sizes, int n_in, void* d_out, int out_size) {
    (void)in_sizes; (void)n_in; (void)out_size;
    static EncodeFn enc = nullptr;
    static int mode = -1;
    if (mode < 0) {
        cudaDriverEntryPointQueryResult qr;
        void* fn = nullptr;
        cudaGetDriverEntryPoint("cuTensorMapEncodeTiled", &fn, cudaEnableDefault, &qr);
        enc = (EncodeFn)fn;
        int dev = 0, sms = 0, occ = 0;
        cudaGetDevice(&dev);
        cudaDeviceGetAttribute(&sms, cudaDevAttrMultiProcessorCount, dev);
        const bool attr_ok =
            cudaFuncSetAttribute(fused_decode_kernel, cudaFuncAttributeMaxDynamicSharedMemorySize, L::SIZE) == cudaSuccess;
        if (attr_ok) cudaOccupancyMaxActiveBlocksPerMultiprocessor(&occ, fused_decode_kernel, NTHREADS, L::SIZE);
        mode = (enc != nullptr && attr_ok && sms * occ >= G) ? 1 : 0;
        (void)cudaGetLastError();
    }
    if (mode == 1) {
        Params p;
        for (int b = 0; b < 2; b++) {
            p.x[b] = (const __nv_bfloat16*)d_in[5 * b + 0];
            encode_kv(enc, &p.km[b], d_in[5 * b + 1]);
            encode_kv(enc, &p.vm[b], d_in[5 * b + 2]);
            encode_wq(enc, &p.wqm[b], d_in[5 * b + 3]);
            p.wo[b] = (const __nv_bfloat16*)d_in[5 * b + 4];
        }
        p.out = (__nv_bfloat16*)d_out;
        fused_decode_kernel<<<G, NTHREADS, L::SIZE>>>(p);
    } else {
        for (int b = 0; b < 2; b++) {
            fb_q_kernel<<<16, 256>>>((const __nv_bfloat16*)d_in[5 * b], (const __nv_bfloat16*)d_in[5 * b + 3], b);
            fb_attn_kernel<<<dim3(FB_SPLIT, 8), 256>>>((const uint4*)d_in[5 * b + 1], (const uint4*)d_in[5 * b + 2], b);
        }
        fb_merge_kernel<<<32, 256>>>();
        for (int b = 0; b < 2; b++)
            fb_out_kernel<<<7, 64>>>((const __nv_bfloat16*)d_in[5 * b + 4], (__nv_bfloat16*)d_out, b);
    }
}
```

```cpp
#include <cuda_runtime.h>
#include <cuda_bf16.h>
#include <cuda.h>
#include <stdint.h>

namespace {

constexpr int G = 132;
constexpr int W = 4;
constexpr int NTHREADS = (W + 2) * 32;
constexpr int TILE_BYTES = 8192;
constexpr int STAGE_BYTES = 2 * TILE_BYTES;
constexpr int TOTAL = 65536;
constexpr int DM = 448;
constexpr int SEG_BYTES = 8 * DM * 2;
constexpr int SLOT_STRIDE = 320;
constexpr int PROG_END = 1 << 30;
constexpr int NS = 12;
constexpr int K0 = 2;
constexpr int Q_DELAY = 1500;
constexpr int MERGE_DELAY = 2500;
constexpr int CAP = 4, CAP_END = 3;
constexpr int END_ZONE = 1000;
#define WO_LAG 1
#define WO_V 1
constexpr unsigned SPIN_LIMIT = 1u << 22;

struct Params {
    const __nv_bfloat16* x[2];
    const __nv_bfloat16* wo[2];
    __nv_bfloat16* out;
    CUtensorMap km[2];
    CUtensorMap vm[2];
    CUtensorMap wqm[2];
};

typedef unsigned long long u64;

__device__ unsigned int g_epoch;
__device__ unsigned int g_ticket;
__device__ ulonglong2 g_q[16 * 2 * 16 * 4];
__device__ uint4 g_po[16 * 32 * G * 4];
__device__ ulonglong2 g_pml[16 * G * 2 * 2];
__device__ uint4 g_ol[2 * 56 * 64 * 2];

#define STAMP(i)

__device__ __forceinline__ uint32_t smem_u32(const void* p) { return (uint32_t)__cvta_generic_to_shared(p); }
__device__ __forceinline__ void mbar_init(uint32_t bar, uint32_t cnt) {
    asm volatile("mbarrier.init.shared::cta.b64 [%0], %1;" ::"r"(bar), "r"(cnt) : "memory");
}
__device__ __forceinline__ void mbar_expect_tx(uint32_t bar, uint32_t bytes) {
    asm volatile("mbarrier.arrive.expect_tx.shared::cta.b64 _, [%0], %1;" ::"r"(bar), "r"(bytes) : "memory");
}
__device__ __forceinline__ void mbar_arrive(uint32_t bar) {
    asm volatile("mbarrier.arrive.shared::cta.b64 _, [%0];" ::"r"(bar) : "memory");
}
__device__ __forceinline__ bool mbar_try(uint32_t bar, uint32_t parity) {
    uint32_t ok;
    asm volatile("{\n.reg .pred p;\nmbarrier.try_wait.parity.shared::cta.b64 p, [%1], %2;\nselp.u32 %0, 1, 0, p;\n}"
                 : "=r"(ok) : "r"(bar), "r"(parity) : "memory");
    return ok != 0;
}
__device__ __forceinline__ void mbar_wait(uint32_t bar, uint32_t parity) {
    unsigned n = 0;
    while (!mbar_try(bar, parity)) {
        if (++n > SPIN_LIMIT) __trap();
    }
}
__device__ __forceinline__ void tma3d(uint32_t dst, const CUtensorMap* m, int row, uint32_t bar, uint64_t pol) {
    asm volatile(
        "cp.async.bulk.tensor.3d.shared::cluster.global.mbarrier::complete_tx::bytes.L2::cache_hint "
        "[%0], [%1, {%3, %4, %3}], [%2], %5;" ::"r"(dst), "l"(m), "r"(bar), "r"(0), "r"(row), "l"(pol)
        : "memory");
}
__device__ __forceinline__ void bulk_load(uint32_t dst, const void* src, uint32_t bytes, uint32_t bar, uint64_t pol) {
    asm volatile(
        "cp.async.bulk.shared::cluster.global.mbarrier::complete_tx::bytes.L2::cache_hint [%0], [%1], %2, [%3], %4;"
        ::"r"(dst), "l"(src), "r"(bytes), "r"(bar), "l"(pol) : "memory");
}
__device__ __forceinline__ uint64_t evict_first_policy() {
    uint64_t pol;
    asm volatile("createpolicy.fractional.L2::evict_first.b64 %0, 1.0;" : "=l"(pol));
    return pol;
}
__device__ __forceinline__ void ldsm4(uint32_t (&r)[4], uint32_t addr) {
    asm volatile("ldmatrix.sync.aligned.m8n8.x4.shared.b16 {%0,%1,%2,%3}, [%4];"
                 : "=r"(r[0]), "=r"(r[1]), "=r"(r[2]), "=r"(r[3]) : "r"(addr) : "memory");
}
__device__ __forceinline__ void ldsm4t(uint32_t (&r)[4], uint32_t addr) {
    asm volatile("ldmatrix.sync.aligned.m8n8.x4.trans.shared.b16 {%0,%1,%2,%3}, [%4];"
                 : "=r"(r[0]), "=r"(r[1]), "=r"(r[2]), "=r"(r[3]) : "r"(addr) : "memory");
}
__device__ __forceinline__ void mma16816(float (&c)[4], const uint32_t (&a)[4], uint32_t b0, uint32_t b1) {
    asm volatile("mma.sync.aligned.m16n8k16.row.col.f32.bf16.bf16.f32 {%0,%1,%2,%3}, {%4,%5,%6,%7}, {%8,%9}, {%0,%1,%2,%3};"
                 : "+f"(c[0]), "+f"(c[1]), "+f"(c[2]), "+f"(c[3])
                 : "r"(a[0]), "r"(a[1]), "r"(a[2]), "r"(a[3]), "r"(b0), "r"(b1));
}
__device__ __forceinline__ uint32_t movtrans(uint32_t a) {
    uint32_t d;
    asm volatile("movmatrix.sync.aligned.m8n8.trans.b16 %0, %1;" : "=r"(d) : "r"(a));
    return d;
}
__device__ __forceinline__ float ex2(float x) {
    float y;
    asm("ex2.approx.ftz.f32 %0, %1;" : "=f"(y) : "f"(x));
    return y;
}
__device__ __forceinline__ uint32_t pack_bf16(float lo, float hi) {
    uint32_t d;
    asm("cvt.rn.bf16x2.f32 %0, %1, %2;" : "=r"(d) : "f"(hi), "f"(lo));
    return d;
}
__device__ __forceinline__ float bf_lo(uint32_t v) { return __uint_as_float(v << 16); }
__device__ __forceinline__ float bf_hi(uint32_t v) { return __uint_as_float(v & 0xffff0000u); }
__device__ __forceinline__ float warp_max(float v) {
    int k = __float_as_int(v);
    k ^= (k >> 31) & 0x7fffffff;
    k = __reduce_max_sync(0xffffffffu, k);
    k ^= (k >> 31) & 0x7fffffff;
    return __int_as_float(k);
}

__device__ __forceinline__ u64 ll_word(uint32_t v, uint32_t tag) { return ((u64)tag << 32) | v; }
__device__ __forceinline__ void ll_store(ulonglong2* p, uint32_t a, uint32_t b, uint32_t tag) {
    asm volatile("st.relaxed.gpu.global.v2.b64 [%0], {%1, %2};" ::"l"(p), "l"(ll_word(a, tag)), "l"(ll_word(b, tag)) : "memory");
}
__device__ __forceinline__ bool ll_ok(u64 x, u64 y, uint32_t tag) {
    return ((uint32_t)(x >> 32) == tag) & ((uint32_t)(y >> 32) == tag);
}
__device__ __forceinline__ uint32_t pt_enc(float v, uint32_t bit) { return (__float_as_uint(v) & ~1u) | bit; }
__device__ __forceinline__ uint32_t xor_or(uint32_t a, uint32_t b, uint32_t m) {
    uint32_t d;
    asm("lop3.b32 %0, %1, %2, %3, 0x7e;" : "=r"(d) : "r"(a), "r"(b), "r"(m));
    return d;
}
__device__ __forceinline__ uint32_t or3(uint32_t a, uint32_t b, uint32_t c) {
    uint32_t d;
    asm("lop3.b32 %0, %1, %2, %3, 0xfe;" : "=r"(d) : "r"(a), "r"(b), "r"(c));
    return d;
}
__device__ __forceinline__ void st128(uint4* p, uint32_t a, uint32_t b, uint32_t c, uint32_t d) {
    asm volatile("{\n.reg .b128 t;\n.reg .b64 lo, hi;\nmov.b64 lo, {%1, %2};\nmov.b64 hi, {%3, %4};\nmov.b128 t, {lo, hi};\n"
                 "st.relaxed.gpu.global.b128 [%0], t;\n}" ::"l"(p), "r"(a), "r"(b), "r"(c), "r"(d) : "memory");
}
__device__ __forceinline__ void ld128(uint4& v, const uint4* p) {
    asm volatile("{\n.reg .b128 t;\n.reg .b64 lo, hi;\nld.relaxed.gpu.global.b128 t, [%4];\nmov.b128 {lo, hi}, t;\n"
                 "mov.b64 {%0, %1}, lo;\nmov.b64 {%2, %3}, hi;\n}"
                 : "=r"(v.x), "=r"(v.y), "=r"(v.z), "=r"(v.w) : "l"(p) : "memory");
}
__device__ __forceinline__ void ld128_stale(uint4& v, const uint4* p, uint32_t bit) {
    asm volatile("{\n.reg .pred p;\n.reg .b32 u;\n.reg .b128 t;\n.reg .b64 lo, hi;\nand.b32 u, %0, 1;\nsetp.ne.u32 p, u, %5;\n"
                 "mov.b64 lo, {%0, %1};\nmov.b64 hi, {%2, %3};\nmov.b128 t, {lo, hi};\n"
                 "@p ld.relaxed.gpu.global.b128 t, [%4];\nmov.b128 {lo, hi}, t;\nmov.b64 {%0, %1}, lo;\nmov.b64 {%2, %3}, hi;\n}"
                 : "+r"(v.x), "+r"(v.y), "+r"(v.z), "+r"(v.w) : "l"(p), "r"(bit) : "memory");
}
__device__ __forceinline__ void st64(void* p, uint32_t a, uint32_t b) {
    asm volatile("{\n.reg .b64 t;\nmov.b64 t, {%1, %2};\nst.relaxed.gpu.global.b64 [%0], t;\n}" ::"l"(p), "r"(a), "r"(b) : "memory");
}
__device__ __forceinline__ void ld2x64(uint4& v, const uint4* p) {
    asm volatile("{\n.reg .b64 lo, hi;\nld.relaxed.gpu.global.v2.b64 {lo, hi}, [%4];\nmov.b64 {%0, %1}, lo;\nmov.b64 {%2, %3}, hi;\n}"
                 : "=r"(v.x), "=r"(v.y), "=r"(v.z), "=r"(v.w) : "l"(p) : "memory");
}
__device__ __forceinline__ void ldu64(u64& v, const void* p) {
    asm volatile("ld.relaxed.gpu.global.b64 %0, [%1];" : "=l"(v) : "l"(p) : "memory");
}
__device__ __forceinline__ void ldu64_stale(u64& v, const void* p, uint32_t bit) {
    asm volatile("{\n.reg .pred p;\n.reg .b32 a, b;\nmov.b64 {a, b}, %0;\nand.b32 b, b, 1;\nsetp.ne.u32 p, b, %2;\n"
                 "@p ld.relaxed.gpu.global.b64 %0, [%1];\n}" : "+l"(v) : "l"(p), "r"(bit) : "memory");
}
__device__ __forceinline__ void mma1688(float (&c)[4], uint32_t a0, uint32_t a1, uint32_t b0) {
    asm volatile("mma.sync.aligned.m16n8k8.row.col.f32.bf16.bf16.f32 {%0,%1,%2,%3}, {%4,%5}, {%6}, {%0,%1,%2,%3};"
                 : "+f"(c[0]), "+f"(c[1]), "+f"(c[2]), "+f"(c[3]) : "r"(a0), "r"(a1), "r"(b0));
}
__device__ __forceinline__ bool ll_load(const ulonglong2* p, uint32_t& a, uint32_t& b, uint32_t tag) {
    u64 x, y;
    asm volatile("ld.relaxed.gpu.global.v2.b64 {%0, %1}, [%2];" : "=l"(x), "=l"(y) : "l"(p) : "memory");
    a = (uint32_t)x;
    b = (uint32_t)y;
    return ll_ok(x, y, tag);
}

struct L {
    static constexpr int RING = 0;
    static constexpr int SLOTS = NS * STAGE_BYTES;
    static constexpr int SLOTML = SLOTS + W * 2 * SLOT_STRIDE * 4;
    static constexpr int RED = SLOTML + W * 16;
    static constexpr int OFIN = RED + W * DM * 4;
    static constexpr int Q0 = OFIN + 64 * 4;
    static constexpr int TK = Q0 + 16 * 128 * 8;
    static constexpr int BARS = TK + 32 * 4;
    static constexpr int NBARS = 3 * NS + 7 + 8;
    static constexpr int SIZE = BARS + NBARS * 8;
};

__global__ void __launch_bounds__(NTHREADS, 1) fused_decode_kernel(const __grid_constant__ Params p) {
    extern __shared__ __align__(1024) unsigned char smem_raw[];
    static_assert(NS % W == 0 && K0 >= 1 && K0 <= NS - 4 && W == 4, "geometry");
    unsigned char* smem = smem_raw;
    const uint32_t sbase = smem_u32(smem);
    const int warp = threadIdx.x >> 5, lane = threadIdx.x & 31;
    const int cta = blockIdx.x;
    const bool has_task = cta < 128;
    const bool isX = has_task && cta >= 64, isY = cta < 64;
    const int slice = cta & 63;

    const uint32_t bar_full = sbase + L::BARS;
    const uint32_t bar_fullv = bar_full + NS * 8;
    const uint32_t bar_empty = bar_fullv + NS * 8;
    const uint32_t bar_ofin = bar_empty + NS * 8;
    const uint32_t bar_q = bar_ofin + 8;
    const uint32_t bar_q2 = bar_q + 8;
    const uint32_t bar_q3 = bar_q2 + 8;
    const uint32_t bar_wq = bar_q3 + 8;
    const uint32_t bar_wo = bar_wq + 8;
    const uint32_t bar_red = bar_wo + 64;
    const uint32_t bar_wqdone = bar_red + 8;
    volatile int* s_tk = reinterpret_cast<volatile int*>(smem + L::TK);
    float* s_slots = reinterpret_cast<float*>(smem + L::SLOTS);
    float* s_slotml = reinterpret_cast<float*>(smem + L::SLOTML);
    float* s_red = reinterpret_cast<float*>(smem + L::RED);
    float* s_ofin = reinterpret_cast<float*>(smem + L::OFIN);
    uint2* s_q0 = reinterpret_cast<uint2*>(smem + L::Q0);

    uint64_t pol = 0;
    auto issue = [&](int s, int t) {
        s_tk[s] = t;
        s_tk[30] = t;
        const uint32_t dst = sbase + L::RING + s * STAGE_BYTES;
        const int b = t >> 15, row = (t & 32767) << 4;
        mbar_expect_tx(bar_full + s * 8, TILE_BYTES);
        tma3d(dst, &p.km[b], row, bar_full + s * 8, pol);
        mbar_expect_tx(bar_fullv + s * 8, TILE_BYTES);
        tma3d(dst + TILE_BYTES, &p.vm[b], row, bar_fullv + s * 8, pol);
    };
    if (threadIdx.x == W * 32) {
        STAMP(0);
        mbar_init(bar_wq, 1);
#pragma unroll
        for (int i = 0; i < K0; i++) { mbar_init(bar_full + i * 8, 1); mbar_init(bar_fullv + i * 8, 1); }
        asm volatile("fence.mbarrier_init.release.cluster;" ::: "memory");
        pol = evict_first_policy();
        if (has_task) {
            mbar_expect_tx(bar_wq, 448 * 128);
#pragma unroll
            for (int i = 0; i < 2; i++)
                asm volatile(
                    "cp.async.bulk.tensor.2d.shared::cluster.global.mbarrier::complete_tx::bytes.L2::cache_hint "
                    "[%0], [%1, {%3, %4}], [%2], %5;" ::"r"(sbase + L::RING + (NS - 4) * STAGE_BYTES + i * 224 * 128),
                    "l"(&p.wqm[cta >> 6]), "r"(bar_wq), "r"((cta & 63) * 64), "r"(i * 224), "l"(pol) : "memory");
        }
#pragma unroll
        for (int i = 0; i < K0; i++) issue(i, cta + G * i);
#pragma unroll
        for (int i = 0; i < L::NBARS; i++)
            if (!(i < K0 || (i >= NS && i < NS + K0) || i == 3 * NS + 4)) mbar_init(bar_full + i * 8, i >= L::NBARS - 2 ? W : 1);
        asm volatile("fence.mbarrier_init.release.cluster;" ::: "memory");
    }

    if (warp == W) {
        __syncwarp();
        asm volatile("bar.arrive 2, %0;" ::"n"(NTHREADS) : "memory");
        if (lane == 0) {
            STAMP(1);
            asm volatile("prefetch.tensormap [%0];" ::"l"(&p.km[1]) : "memory");
            asm volatile("prefetch.tensormap [%0];" ::"l"(&p.vm[1]) : "memory");
        }
        pol = evict_first_policy();
        int s = K0, cnt = K0, t = 0;
        uint32_t ph = 1;
        bool first_lap = has_task;
        while (true) {
            const int cap = (t >= TOTAL - END_ZONE) ? CAP_END : CAP;
            if (cnt >= cap) {
                int sd = s - cap;
                uint32_t pd = ph ^ 1;
                if (sd < 0) { sd += NS; pd ^= 1; }
                mbar_wait(bar_full + sd * 8, pd);
            }
            cnt++;
            unsigned v = 0;
            if (lane == 0) asm volatile("atom.relaxed.gpu.global.inc.u32 %0, [%1], 0x7fffffff;" : "=r"(v) : "l"(&g_ticket) : "memory");
            mbar_wait(bar_empty + s * 8, ph);
            if (first_lap && s == NS - 4) { mbar_wait(bar_wqdone, 0); first_lap = false; }
            t = (int)__shfl_sync(0xffffffffu, v, 0) + G * K0;
            if (t >= TOTAL) break;
            const uint32_t dst = sbase + L::RING + s * STAGE_BYTES;
            const int b = t >> 15;
            asm volatile(
                "{\n.reg .pred p;\nelect.sync _|p, 0xffffffff;\n"
                "@p st.volatile.shared.u32 [%8], %9;\n"
                "@p st.volatile.shared.u32 [%10], %9;\n"
                "@p mbarrier.arrive.expect_tx.shared::cta.b64 _, [%3], 8192;\n"
                "@p cp.async.bulk.tensor.3d.shared::cluster.global.mbarrier::complete_tx::bytes.L2::cache_hint "
                "[%0], [%1, {%5, %6, %5}], [%3], %7;\n"
                "@p mbarrier.arrive.expect_tx.shared::cta.b64 _, [%4], 8192;\n"
                "@p cp.async.bulk.tensor.3d.shared::cluster.global.mbarrier::complete_tx::bytes.L2::cache_hint "
                "[%11], [%2, {%5, %6, %5}], [%4], %7;\n}"
                ::"r"(dst), "l"(&p.km[b]), "l"(&p.vm[b]), "r"(bar_full + s * 8), "r"(bar_fullv + s * 8), "r"(0),
                  "r"((t & 32767) << 4), "l"(pol), "r"(sbase + L::TK + s * 4), "r"(t), "r"(sbase + L::TK + 30 * 4),
                  "r"(dst + TILE_BYTES) : "memory");
            if (++s == NS) { s = 0; ph ^= 1; }
        }
        if (lane == 0) {
            STAMP(2);
            s_tk[30] = PROG_END;
            s_tk[31] = s;
        }
        __syncwarp();
        if (lane < W) {
            int sj = s + lane;
            uint32_t pj = ph;
            if (sj >= NS) { sj -= NS; pj ^= 1; }
            mbar_wait(bar_empty + sj * 8, pj);
            s_tk[sj] = TOTAL;
            mbar_arrive(bar_full + sj * 8);
        }
        __syncwarp();
        if (isY) {
            mbar_wait(bar_wqdone, 0);
            if (cnt - 1 > WO_LAG) {
                int sd = s - 1 - WO_LAG;
                uint32_t pd = ph ^ 1;
                if (sd < 0) { sd += NS; pd ^= 1; }
                mbar_wait((WO_V ? bar_fullv : bar_full) + sd * 8, pd);
            }
            if (lane == 0) STAMP(9);
            const char* src = reinterpret_cast<const char*>(p.wo[0]) + (size_t)slice * SEG_BYTES;
#pragma unroll
            for (int k = 0; k < 8; k++) {
                int ws = s + (k >> 1);
                if (ws >= NS) ws -= NS;
                asm volatile(
                    "{\n.reg .pred p;\nelect.sync _|p, 0xffffffff;\n"
                    "@p mbarrier.arrive.expect_tx.shared::cta.b64 _, [%2], %3;\n"
                    "@p cp.async.bulk.shared::cluster.global.mbarrier::complete_tx::bytes.L2::cache_hint [%0], [%1], %3, [%2], %4;\n}"
                    ::"r"(sbase + L::RING + ws * STAGE_BYTES + (k & 1) * SEG_BYTES), "l"(src + (size_t)k * 64 * SEG_BYTES),
                      "r"(bar_wo + k * 8), "r"(SEG_BYTES), "l"(pol) : "memory");
            }
        }
    } else if (warp == W + 1) {
        uint32_t tag;
        asm volatile("ld.relaxed.gpu.global.u32 %0, [%1];" : "=r"(tag) : "l"(&g_epoch) : "memory");
        tag += 1;
        auto wait_progress = [&](int target) {
            unsigned n = 0;
            while (s_tk[30] < target) {
                __nanosleep(100);
                if (++n > SPIN_LIMIT) __trap();
            }
        };
        {
            bool synced = false;
#pragma unroll 1
            for (int h = 0; h < 16; h++) {
                if (h == 1) wait_progress(Q_DELAY);
                unsigned n = 0;
                uint32_t qa[4], qb[4];
                while (true) {
                    bool ok = true;
#pragma unroll
                    for (int i = 0; i < 4; i++) ok &= ll_load(g_q + h * 128 + i * 32 + lane, qa[i], qb[i], tag);
                    if (!synced) {
                        asm volatile("bar.sync 2, %0;" ::"n"(NTHREADS) : "memory");
                        if (has_task) mbar_wait(bar_wqdone, 0);
                        synced = true;
                    }
                    if (__all_sync(0xffffffffu, ok)) break;
                    if (++n > SPIN_LIMIT) __trap();
                }
#pragma unroll
                for (int i = 0; i < 4; i++) s_q0[h * 128 + i * 32 + lane] = make_uint2(qa[i], qb[i]);
                __syncwarp();
                if (lane == 0) {
                    if (h == 0) mbar_arrive(bar_q);
                    if (h == 3) mbar_arrive(bar_q2);
                    if (h == 15) mbar_arrive(bar_q3);
                }
            }
        }
        if (has_task) {
            const uint32_t bit = tag & 1u, bitmask = 0u - bit;
            const int qh = slice >> 5;
            const int g = lane >> 2, t4 = lane & 3;
            pol = evict_first_policy();
            float y[7][4];
#pragma unroll
            for (int j = 0; j < 7; j++) { y[j][0] = 0.f; y[j][1] = 0.f; y[j][2] = 0.f; y[j][3] = 0.f; }
#pragma unroll 1
            for (int h = isX ? 8 : 0; h < 16; h = (h == 7) ? 14 : h + 1) {
                if (isX || h < 8) {
                    uint32_t wf[14][4];
                    if (isX) {
                        wait_progress(h * 4096);
                        if (lane == 0) {
                            asm volatile("fence.proxy.async.shared::cta;" ::: "memory");
                            mbar_expect_tx(bar_wo + (h & 7) * 8, SEG_BYTES);
                            bulk_load(sbase + L::RED,
                                      reinterpret_cast<const char*>(p.wo[1]) + (size_t)((h & 7) * 64 + slice) * SEG_BYTES,
                                      SEG_BYTES, bar_wo + (h & 7) * 8, pol);
                        }
                        mbar_wait(bar_wo + (h & 7) * 8, 0);
                        const int r = lane & 7, row = 4 * ((r >> 1) & 1) + 2 * (r >> 2) + (r & 1);
                        const uint32_t wa = sbase + L::RED + row * (DM * 2) + (lane >> 3) * 16;
#pragma unroll
                        for (int x = 0; x < 14; x++) ldsm4t(wf[x], wa + x * 64);
                        __syncwarp();
                    }
                    wait_progress(h < 15 ? (h + 1) * 4096 + MERGE_DELAY : PROG_END);
                    u64 ml[5];
                    uint4 ov[9];
                    const ulonglong2* pml = g_pml + ((h * G + lane) * 2 + qh) * 2;
                    const uint4* pr = g_po + ((size_t)(h * 32 + (slice >> 1)) * G + (lane >> 1)) * 4 + (slice & 1) * 2 + (lane & 1);
                    constexpr int PRS = 16 * 4;
                    const ulonglong2* pml4 = pml + (lane < G - 128 ? 4 * 128 : 0);
                    const uint4* pr8 = pr + (lane < (G - 128) * 2 ? 8 * PRS : 0);
#pragma unroll
                    for (int j = 0; j < 5; j++) ldu64(ml[j], j < 4 ? pml + j * 128 : pml4);
#pragma unroll
                    for (int it = 0; it < 9; it++) ld128(ov[it], it < 8 ? pr + it * PRS : pr8);
                    unsigned n = 0;
                    while (true) {
                        const uint32_t bad = or3(
                            or3(xor_or((uint32_t)(ml[0] >> 32), (uint32_t)(ml[1] >> 32), bitmask),
                                xor_or((uint32_t)(ml[2] >> 32), (uint32_t)(ml[3] >> 32), bitmask),
                                xor_or((uint32_t)(ml[4] >> 32), ov[0].x, bitmask)),
                            or3(xor_or(ov[1].x, ov[2].x, bitmask), xor_or(ov[3].x, ov[4].x, bitmask), xor_or(ov[5].x, ov[6].x, bitmask)),
                            xor_or(ov[7].x, ov[8].x, bitmask));
                        if (__all_sync(0xffffffffu, (bad & 1u) == 0) && (h == 15 || n > 0)) break;
                        if (h != 15) __nanosleep(400);
                        if (++n > SPIN_LIMIT) __trap();
#pragma unroll
                        for (int j = 0; j < 5; j++) ldu64_stale(ml[j], j < 4 ? pml + j * 128 : pml4, bit);
#pragma unroll
                        for (int it = 0; it < 9; it++) ld128_stale(ov[it], it < 8 ? pr + it * PRS : pr8, bit);
                    }
                    if (lane == 0) STAMP(32 + h);
                    float mj[5];
#pragma unroll
                    for (int j = 0; j < 5; j++) mj[j] = __uint_as_float((uint32_t)ml[j]);
                    const float M = warp_max(fmaxf(fmaxf(fmaxf(mj[0], mj[1]), fmaxf(mj[2], mj[3])), mj[4]));
                    float wc[5], Ls = 0.f;
#pragma unroll
                    for (int j = 0; j < 5; j++) {
                        wc[j] = ex2(mj[j] - M);
                        if (j == 4 && lane >= G - 128) wc[j] = 0.f;
                        Ls += wc[j] * __uint_as_float((uint32_t)(ml[j] >> 32));
                    }
                    float a0 = 0.f, a1 = 0.f, a2 = 0.f, a3 = 0.f;
#pragma unroll
                    for (int it = 0; it < 9; it++) {
                        const float wv = __shfl_sync(0xffffffffu, wc[it >> 1], 16 * (it & 1) + (lane >> 1));
                        a0 += wv * __uint_as_float(ov[it].x);
                        a1 += wv * __uint_as_float(ov[it].y);
                        a2 += wv * __uint_as_float(ov[it].z);
                        a3 += wv * __uint_as_float(ov[it].w);
                        if (it == 0) Ls += __shfl_xor_sync(0xffffffffu, Ls, 1);
                    }
                    const bool up = lane & 2;
                    float ax = (up ? a2 : a0) + __shfl_xor_sync(0xffffffffu, up ? a0 : a2, 2);
                    float ay = (up ? a3 : a1) + __shfl_xor_sync(0xffffffffu, up ? a1 : a3, 2);
                    Ls += __shfl_xor_sync(0xffffffffu, Ls, 2);
#pragma unroll
                    for (int o = 4; o <= 16; o <<= 1) {
                        ax += __shfl_xor_sync(0xffffffffu, ax, o);
                        ay += __shfl_xor_sync(0xffffffffu, ay, o);
                        Ls += __shfl_xor_sync(0xffffffffu, Ls, o);
                    }
                    float inv;
                    asm("rcp.approx.ftz.f32 %0, %1;" : "=f"(inv) : "f"(Ls));
                    const uint32_t o2 = pack_bf16(ax * inv, ay * inv);
                    if (isY) {
                        if (lane < 4)
                            *reinterpret_cast<float2*>(s_ofin + h * 8 + 4 * (lane & 1) + (lane & 2)) = make_float2(bf_lo(o2), bf_hi(o2));
                        __syncwarp();
                        if (h == 7 && lane == 0) mbar_arrive(bar_ofin);
                    } else {
                        if (lane == 0) STAMP(3);
#pragma unroll
                        for (int q = 0; q < 4; q++) {
                            const uint32_t bq = (g == 2 * q) ? o2 : 0u;
#pragma unroll
                            for (int j = 0; j < 7; j++) {
                                const int i = 4 * j + q;
                                mma1688(y[j], wf[i >> 1][2 * (i & 1)], wf[i >> 1][2 * (i & 1) + 1], bq);
                            }
                        }
                    }
                }
                if (h >= 14) {
                    const bool real = (h == 15);
                    const uint32_t obit = real ? bit : bit ^ 1u;
                    char* dst = reinterpret_cast<char*>(g_ol + ((size_t)((isX ? 56 : 0) + g) * 64 + slice) * 2) + t4 * 8;
                    if (isX) {
#pragma unroll
                        for (int j = 0; j < 7; j++) st64(dst + (size_t)j * 8 * 64 * 32, pt_enc(y[j][0], obit), __float_as_uint(y[j][2]));
                        if (lane == 0) STAMP(4);
                    } else {
                        if (real) mbar_wait(bar_red, 0); else wait_progress(14 * 4096);
                        if (lane == 0) STAMP(5);
#pragma unroll
                        for (int j = 0; j < 7; j++) {
                            float vx = 0.f, vy = 0.f;
#pragma unroll
                            for (int w = 0; w < W; w++) {
                                const float2 v = *reinterpret_cast<const float2*>(s_red + w * DM + 64 * j + 2 * lane);
                                vx += v.x;
                                vy += v.y;
                            }
                            st64(dst + (size_t)j * 8 * 64 * 32, pt_enc(vx, obit), __float_as_uint(vy));
                        }
                        if (lane == 0) STAMP(11);
                    }
                }
            }
            if (cta == 127 && lane == 0) {
                asm volatile("st.relaxed.gpu.global.u32 [%0], %1;" ::"l"(&g_ticket), "r"(0u) : "memory");
                asm volatile("st.relaxed.gpu.global.u32 [%0], %1;" ::"l"(&g_epoch), "r"(tag) : "memory");
            }
        }
    } else {
        uint32_t tag;
        asm volatile("ld.relaxed.gpu.global.u32 %0, [%1];" : "=r"(tag) : "l"(&g_epoch) : "memory");
        const int g = lane >> 2, t4 = lane & 3;
        if (has_task) {
            const int tb = cta >> 6, qs = cta & 63;
            const int r = threadIdx.x >> 3, c8 = threadIdx.x & 7;
            const uint2* xp = reinterpret_cast<const uint2*>(p.x[tb] + 28 * r);
            uint2 xv[7];
#pragma unroll
            for (int i = 0; i < 7; i++)
                asm volatile("ld.global.nc.v2.u32 {%0,%1}, [%2];" : "=r"(xv[i].x), "=r"(xv[i].y) : "l"(xp + i));
            asm volatile("bar.sync 2, %0;" ::"n"(NTHREADS) : "memory");
            mbar_wait(bar_wq, 0);
            const uint4* wv = reinterpret_cast<const uint4*>(smem + L::RING + (NS - 4) * STAGE_BYTES) + 28 * r * 8 + c8;
            float acc[8];
#pragma unroll
            for (int j = 0; j < 8; j++) acc[j] = 0.f;
#pragma unroll
            for (int i = 0; i < 28; i++) {
                const uint32_t xw = (i & 2) ? xv[i >> 2].y : xv[i >> 2].x;
                const float xs = (i & 1) ? bf_hi(xw) : bf_lo(xw);
                const uint4 v = wv[i * 8];
                acc[0] += xs * bf_lo(v.x); acc[1] += xs * bf_hi(v.x);
                acc[2] += xs * bf_lo(v.y); acc[3] += xs * bf_hi(v.y);
                acc[4] += xs * bf_lo(v.z); acc[5] += xs * bf_hi(v.z);
                acc[6] += xs * bf_lo(v.w); acc[7] += xs * bf_hi(v.w);
            }
#pragma unroll
            for (int j = 0; j < 8; j++) {
                acc[j] += __shfl_xor_sync(0xffffffffu, acc[j], 8);
                acc[j] += __shfl_xor_sync(0xffffffffu, acc[j], 16);
            }
            if (lane < 8) {
                float4* d = reinterpret_cast<float4*>(s_red + warp * 64 + lane * 8);
                d[0] = make_float4(acc[0], acc[1], acc[2], acc[3]);
                d[1] = make_float4(acc[4], acc[5], acc[6], acc[7]);
            }
            asm volatile("bar.sync 1, %0;" ::"n"(W * 32) : "memory");
            if (threadIdx.x < 16) {
                const int il = threadIdx.x >> 2;
                float q[4];
#pragma unroll
                for (int k = 0; k < 4; k++) {
                    const int d = 16 * il + 2 * t4 + (k & 1) + 8 * (k >> 1);
                    q[k] = 0.f;
#pragma unroll
                    for (int w = 0; w < W; w++) q[k] += s_red[w * 64 + d];
                }
                ll_store(g_q + ((tb * 16 + (qs >> 2)) * 16 + (qs & 3) * 4 + il) * 4 + t4,
                         pack_bf16(q[0], q[1]), pack_bf16(q[2], q[3]), tag + 1);
            }
            __syncwarp();
            if (lane == 0) mbar_arrive(bar_wqdone);
            if (threadIdx.x == 0) STAMP(6);
        } else {
            asm volatile("bar.sync 2, %0;" ::"n"(NTHREADS) : "memory");
        }
        tag += 1;
        const uint32_t bit = tag & 1u;

        float acc[4][4];
#pragma unroll
        for (int i = 0; i < 4; i++) { acc[i][0] = 0.f; acc[i][1] = 0.f; acc[i][2] = 0.f; acc[i][3] = 0.f; }
        float m0 = -INFINITY, m1 = -INFINITY;
        float lacc[4] = {0.f, 0.f, 0.f, 0.f};
        const uint32_t ones[4] = {0x3f803f80u, 0x3f803f80u, 0x3f803f80u, 0x3f803f80u};
        uint32_t qf[16][2];
        int cur = 0;
        const uint32_t krow = (lane & 7) + 8 * ((lane >> 3) & 1), vrow = (lane & 7) + 8 * (lane >> 4);
        const uint32_t koff = krow * 128 + (((lane >> 4) ^ (krow & 7)) << 4);
        const uint32_t voff = TILE_BYTES + vrow * 128 + ((((lane >> 3) & 1) ^ (vrow & 7)) << 4);
        const float SC = 0.0625f * 1.4426950408889634f;
        int s = warp;
        uint32_t ph = 0;
        mbar_wait(bar_q, 0);
#pragma unroll
        for (int i = 0; i < 16; i++) {
            const uint2 v = s_q0[((g & 1) * 16 + i) * 4 + t4];
            qf[i][0] = v.x;
            qf[i][1] = v.y;
        }
        if (threadIdx.x == 0) STAMP(7);
        while (true) {
            mbar_wait(bar_full + s * 8, ph);
            const int t = s_tk[s];
            const int h = t >> 12;
            if (h != cur) {
                while (cur < h) {
                    float* sl = s_slots + warp * 2 * SLOT_STRIDE + 16 * t4 + 8 * (t4 >> 1) + g;
                    if (lane == 0) *reinterpret_cast<float4*>(s_slotml + warp * 4) = make_float4(m0, lacc[0], m1, lacc[1]);
#pragma unroll
                    for (int j = 0; j < 4; j++) {
                        sl[80 * j] = acc[j][0];
                        sl[80 * j + SLOT_STRIDE] = acc[j][1];
                        sl[80 * j + 8] = acc[j][2];
                        sl[80 * j + 8 + SLOT_STRIDE] = acc[j][3];
                    }
                    uint4* po = g_po + ((size_t)(cur * 32 + 8 * warp + (lane >> 2)) * G + cta) * 4 + (lane & 3);
                    ulonglong2* pml = g_pml + ((cur * G + cta) * 2 + (warp >> 1)) * 2 + lane;
                    asm volatile("bar.sync 1, %0;" ::"n"(W * 32) : "memory");
                    if (threadIdx.x == 0) STAMP(16 + cur);
                    float2 mlw[W];
                    float4 sv[W];
                    float M = -INFINITY;
#pragma unroll
                    for (int w = 0; w < W; w++) {
                        mlw[w] = *reinterpret_cast<const float2*>(s_slotml + w * 4 + (warp & 2));
                        sv[w] = *reinterpret_cast<const float4*>(s_slots + (w * 2 + (warp >> 1)) * SLOT_STRIDE + 160 * (warp & 1) + 4 * lane + (lane & 24));
                        M = fmaxf(M, mlw[w].x);
                    }
                    const float R = (M == -INFINITY) ? 0.f : M;
                    float4 o = make_float4(0.f, 0.f, 0.f, 0.f);
                    float Lw = 0.f;
#pragma unroll
                    for (int w = 0; w < W; w++) {
                        const float f = ex2(mlw[w].x - R);
                        Lw += f * mlw[w].y;
                        o.x += f * sv[w].x; o.y += f * sv[w].y; o.z += f * sv[w].z; o.w += f * sv[w].w;
                    }
                    st128(po, pt_enc(o.x, bit), __float_as_uint(o.y), __float_as_uint(o.z), __float_as_uint(o.w));
                    const bool mlwriter = !(warp & 1) && lane < 2;
                    if (mlwriter) ll_store(pml, __float_as_uint(M), __float_as_uint(M), pt_enc(Lw, bit));
                    if (cur == 15 && threadIdx.x == 0) STAMP(13);
                    if (cur == 13) {
                        st128(po + 2 * 32 * G * 4, bit ^ 1u, 0u, 0u, 0u);
                        if (mlwriter) ll_store(pml + 2 * G * 4, 0u, 0u, bit ^ 1u);
                    }
#pragma unroll
                    for (int i = 0; i < 4; i++) { acc[i][0] = 0.f; acc[i][1] = 0.f; acc[i][2] = 0.f; acc[i][3] = 0.f; }
                    m0 = -INFINITY; m1 = -INFINITY;
                    lacc[0] = 0.f; lacc[1] = 0.f; lacc[2] = 0.f; lacc[3] = 0.f;
                    cur++;
                    asm volatile("bar.sync 1, %0;" ::"n"(W * 32) : "memory");
                }
                if (h >= 16) break;
                mbar_wait(h > 3 ? bar_q3 : bar_q2, 0);
#pragma unroll
                for (int i = 0; i < 16; i++) {
                    const uint2 v = s_q0[h * 128 + ((g & 1) * 16 + i) * 4 + t4];
                    qf[i][0] = v.x;
                    qf[i][1] = v.y;
                }
            }
            const uint32_t stage = sbase + L::RING + s * STAGE_BYTES;
            float sc[4][4];
#pragma unroll
            for (int c = 0; c < 4; c++) { sc[c][0] = 0.f; sc[c][1] = 0.f; sc[c][2] = 0.f; sc[c][3] = 0.f; }
            const uint32_t kb = stage + koff;
#pragma unroll
            for (int i = 0; i < 16; i++) {
                uint32_t a[4];
                ldsm4(a, (kb ^ ((i & 3) << 5)) + (i >> 2) * 2048);
                mma16816(sc[i & 3], a, qf[i][0], qf[i][1]);
            }
            const float s0 = ((sc[0][0] + sc[1][0]) + (sc[2][0] + sc[3][0])) * SC;
            const float s1 = ((sc[0][1] + sc[1][1]) + (sc[2][1] + sc[3][1])) * SC;
            const float s2 = ((sc[0][2] + sc[1][2]) + (sc[2][2] + sc[3][2])) * SC;
            const float s3 = ((sc[0][3] + sc[1][3]) + (sc[2][3] + sc[3][3])) * SC;
            float n0 = fmaxf(s0, s2), n1 = fmaxf(s1, s3);
            if (__any_sync(0xffffffffu, (n0 > m0) | (n1 > m1))) {
                n0 = fmaxf(warp_max(n0), m0);
                n1 = fmaxf(warp_max(n1), m1);
                const float f0 = ex2(m0 - n0), f1 = ex2(m1 - n1);
                m0 = n0; m1 = n1;
                lacc[0] *= f0; lacc[1] *= f1; lacc[2] *= f0; lacc[3] *= f1;
#pragma unroll
                for (int i = 0; i < 4; i++) { acc[i][0] *= f0; acc[i][1] *= f1; acc[i][2] *= f0; acc[i][3] *= f1; }
            }
            const float p0 = ex2(s0 - m0), p1 = ex2(s1 - m1), p2 = ex2(s2 - m0), p3 = ex2(s3 - m1);
            const uint32_t b0 = movtrans(pack_bf16(p0, p1));
            const uint32_t b1 = movtrans(pack_bf16(p2, p3));
            mma16816(lacc, ones, b0, b1);
            mbar_wait(bar_fullv + s * 8, ph);
            const uint32_t vb = stage + voff;
#pragma unroll
            for (int q = 0; q < 4; q++) {
                const uint32_t c0 = ((g >> 1) == q) ? b0 : 0u, c1 = ((g >> 1) == q) ? b1 : 0u;
#pragma unroll
                for (int j = 0; j < 4; j++) {
                    uint32_t a[4];
                    ldsm4t(a, (vb ^ (q << 5)) + j * 2048);
                    mma16816(acc[j], a, c0, c1);
                }
            }
            __syncwarp();
            if (lane == 0) mbar_arrive(bar_empty + s * 8);
            s += W;
            if (s >= NS) { s -= NS; ph ^= 1; }
        }

        if (isY) {
            mbar_wait(bar_ofin, 0);
            const int ws0 = s_tk[31];
            float a[7][2];
#pragma unroll
            for (int j = 0; j < 7; j++) { a[j][0] = 0.f; a[j][1] = 0.f; }
#pragma unroll 1
            for (int k = warp; k < 8; k += W) {
                int ws = ws0 + (k >> 1);
                if (ws >= NS) ws -= NS;
                const uint32_t* wseg =
                    reinterpret_cast<const uint32_t*>(smem + L::RING + ws * STAGE_BYTES + (k & 1) * SEG_BYTES);
                mbar_wait(bar_wo + k * 8, 0);
#pragma unroll
                for (int r = 0; r < 8; r++) {
                    const float o = s_ofin[k * 8 + r];
#pragma unroll
                    for (int j = 0; j < 7; j++) {
                        const uint32_t wv = wseg[r * (DM / 2) + 32 * j + lane];
                        a[j][0] += o * bf_lo(wv);
                        a[j][1] += o * bf_hi(wv);
                    }
                }
            }
#pragma unroll
            for (int j = 0; j < 7; j++)
                *reinterpret_cast<float2*>(s_red + warp * DM + 64 * j + 2 * lane) = make_float2(a[j][0], a[j][1]);
            __syncwarp();
            if (lane == 0) mbar_arrive(bar_red);
        }
        if (isX && slice < 56 && !(warp & 1)) {
            const bool fb = warp < 2;
            const uint32_t bitmask = 0u - bit;
            const uint4* src = g_ol + (size_t)((fb ? 56 : 0) + slice) * 64 * 2 + lane;
            const int et = 2 * (lane & 1) + ((lane >> 1) & 1), es = (lane >> 2) & 1;
            const int col = fb ? DM + 64 * (slice >> 3) + 16 * et + 8 * es + (slice & 7) : 8 * slice + 2 * et + es;
            __nv_bfloat16* dst = p.out + col;
            unsigned n = 0;
            while (true) {
                uint4 v[4];
#pragma unroll
                for (int i = 0; i < 4; i++) ld2x64(v[i], src + i * 32);
                const uint32_t bad = or3(xor_or(v[0].x, v[0].z, bitmask), xor_or(v[1].x, v[1].z, bitmask),
                                         xor_or(v[2].x, v[2].z, bitmask)) | xor_or(v[3].x, v[3].z, bitmask);
                const bool done = __all_sync(0xffffffffu, (bad & 1u) == 0);
                const float a0 = (__uint_as_float(v[0].x) + __uint_as_float(v[1].x)) + (__uint_as_float(v[2].x) + __uint_as_float(v[3].x));
                const float a1 = (__uint_as_float(v[0].y) + __uint_as_float(v[1].y)) + (__uint_as_float(v[2].y) + __uint_as_float(v[3].y));
                const float a2 = (__uint_as_float(v[0].z) + __uint_as_float(v[1].z)) + (__uint_as_float(v[2].z) + __uint_as_float(v[3].z));
                const float a3 = (__uint_as_float(v[0].w) + __uint_as_float(v[1].w)) + (__uint_as_float(v[2].w) + __uint_as_float(v[3].w));
                if (done || n == 0) {
                    const bool u1 = lane & 2, u2 = lane & 4;
                    const float bx = (u1 ? a2 : a0) + __shfl_xor_sync(0xffffffffu, u1 ? a0 : a2, 2);
                    const float by = (u1 ? a3 : a1) + __shfl_xor_sync(0xffffffffu, u1 ? a1 : a3, 2);
                    float c = (u2 ? by : bx) + __shfl_xor_sync(0xffffffffu, u2 ? bx : by, 4);
                    c += __shfl_xor_sync(0xffffffffu, c, 8);
                    c += __shfl_xor_sync(0xffffffffu, c, 16);
                    if (done && lane < 8) *dst = __float2bfloat16(c);
                    if (done) break;
                }
                if (++n > SPIN_LIMIT) __trap();
            }
            if (lane == 0 && !(warp & 1)) STAMP(fb ? 8 : 12);
        }
    }
}

constexpr int FB_SPLIT = 64;
__device__ float g_fq[2 * 4096];
__device__ float g_fp[16 * FB_SPLIT * 8 * 2 * 264];

__global__ void fb_q_kernel(const __nv_bfloat16* x, const __nv_bfloat16* wq, int b) {
    const int n = blockIdx.x * blockDim.x + threadIdx.x;
    float a = 0.f;
    for (int k = 0; k < DM; k++) a += __bfloat162float(x[k]) * __bfloat162float(wq[(size_t)k * 4096 + n]);
    g_fq[b * 4096 + n] = __bfloat162float(__float2bfloat16(a));
}
__global__ void fb_attn_kernel(const uint4* k, const uint4* v, int b) {
    const int hk = blockIdx.y, warp = threadIdx.x >> 5, lane = threadIdx.x & 31;
    float q[2][8], o[2][8], m[2] = {-INFINITY, -INFINITY}, l[2] = {0.f, 0.f};
    for (int h = 0; h < 2; h++)
        for (int j = 0; j < 8; j++) { q[h][j] = g_fq[b * 4096 + (hk * 2 + h) * 256 + lane * 8 + j]; o[h][j] = 0.f; }
    const int n = 65536 / FB_SPLIT / 8;
    const size_t row0 = (size_t)hk * 65536 + (size_t)(blockIdx.x * 8 + warp) * n;
    for (int i = 0; i < n; i++) {
        const uint4 kk = k[(row0 + i) * 32 + lane], vv = v[(row0 + i) * 32 + lane];
        const float kf[8] = {bf_lo(kk.x), bf_hi(kk.x), bf_lo(kk.y), bf_hi(kk.y), bf_lo(kk.z), bf_hi(kk.z), bf_lo(kk.w), bf_hi(kk.w)};
        const float vf[8] = {bf_lo(vv.x), bf_hi(vv.x), bf_lo(vv.y), bf_hi(vv.y), bf_lo(vv.z), bf_hi(vv.z), bf_lo(vv.w), bf_hi(vv.w)};
#pragma unroll
        for (int h = 0; h < 2; h++) {
            float s = 0.f;
#pragma unroll
            for (int j = 0; j < 8; j++) s += q[h][j] * kf[j];
            for (int d = 16; d >= 1; d >>= 1) s += __shfl_xor_sync(0xffffffffu, s, d);
            s *= 0.0625f * 1.4426950408889634f;
            const float mn = fmaxf(m[h], s), f = ex2(m[h] - mn), pr = ex2(s - mn);
            m[h] = mn;
            l[h] = l[h] * f + pr;
#pragma unroll
            for (int j = 0; j < 8; j++) o[h][j] = o[h][j] * f + pr * vf[j];
        }
    }
    for (int h = 0; h < 2; h++) {
        float* d = g_fp + ((((size_t)(b * 8 + hk) * FB_SPLIT + blockIdx.x) * 8 + warp) * 2 + h) * 264;
        for (int j = 0; j < 8; j++) d[lane * 8 + j] = o[h][j];
        if (lane == 0) { d[256] = m[h]; d[257] = l[h]; }
    }
}
__global__ void fb_merge_kernel() {
    const int hq = blockIdx.x;
    const float* base = g_fp + ((size_t)(hq >> 1) * FB_SPLIT * 8 * 2 + (hq & 1)) * 264;
    float M = -INFINITY, Ls = 0.f, a = 0.f;
    for (int i = 0; i < FB_SPLIT * 8; i++) M = fmaxf(M, base[(size_t)i * 528 + 256]);
    for (int i = 0; i < FB_SPLIT * 8; i++) {
        const float w = ex2(base[(size_t)i * 528 + 256] - M);
        Ls += w * base[(size_t)i * 528 + 257];
        a += w * base[(size_t)i * 528 + threadIdx.x];
    }
    g_fq[hq * 256 + threadIdx.x] = __bfloat162float(__float2bfloat16(a / Ls));
}
__global__ void fb_out_kernel(const __nv_bfloat16* wo, __nv_bfloat16* out, int b) {
    const int n = blockIdx.x * 64 + threadIdx.x;
    float a = 0.f;
    for (int k = 0; k < 4096; k++) a += g_fq[b * 4096 + k] * __bfloat162float(wo[(size_t)k * DM + n]);
    out[b * DM + n] = __float2bfloat16(a);
}

typedef CUresult (*EncodeFn)(CUtensorMap*, CUtensorMapDataType, cuuint32_t, void*, const cuuint64_t*, const cuuint64_t*,
                             const cuuint32_t*, const cuuint32_t*, CUtensorMapInterleave, CUtensorMapSwizzle,
                             CUtensorMapL2promotion, CUtensorMapFloatOOBfill);

void encode_kv(EncodeFn enc, CUtensorMap* m, const void* ptr) {
    cuuint64_t gd[3] = {64, 8ull * 65536ull, 4};
    cuuint64_t gs[2] = {512, 128};
    cuuint32_t box[3] = {64, 16, 4};
    cuuint32_t es[3] = {1, 1, 1};
    enc(m, CU_TENSOR_MAP_DATA_TYPE_BFLOAT16, 3, const_cast<void*>(ptr), gd, gs, box, es, CU_TENSOR_MAP_INTERLEAVE_NONE,
        CU_TENSOR_MAP_SWIZZLE_128B, CU_TENSOR_MAP_L2_PROMOTION_L2_256B, CU_TENSOR_MAP_FLOAT_OOB_FILL_NONE);
}

void encode_wq(EncodeFn enc, CUtensorMap* m, const void* ptr) {
    cuuint64_t gd[2] = {4096, 448};
    cuuint64_t gs[1] = {8192};
    cuuint32_t box[2] = {64, 224};
    cuuint32_t es[2] = {1, 1};
    enc(m, CU_TENSOR_MAP_DATA_TYPE_BFLOAT16, 2, const_cast<void*>(ptr), gd, gs, box, es, CU_TENSOR_MAP_INTERLEAVE_NONE,
        CU_TENSOR_MAP_SWIZZLE_NONE, CU_TENSOR_MAP_L2_PROMOTION_L2_128B, CU_TENSOR_MAP_FLOAT_OOB_FILL_NONE);
}

}

extern "C" void kernel_launch(void* const* d_in, const int* in_sizes, int n_in, void* d_out, int out_size) {
    (void)in_sizes; (void)n_in; (void)out_size;
    static EncodeFn enc = nullptr;
    static int mode = -1;
    if (mode < 0) {
        cudaDriverEntryPointQueryResult qr;
        void* fn = nullptr;
        cudaGetDriverEntryPoint("cuTensorMapEncodeTiled", &fn, cudaEnableDefault, &qr);
        enc = (EncodeFn)fn;
        int dev = 0, sms = 0, occ = 0;
        cudaGetDevice(&dev);
        cudaDeviceGetAttribute(&sms, cudaDevAttrMultiProcessorCount, dev);
        const bool attr_ok =
            cudaFuncSetAttribute(fused_decode_kernel, cudaFuncAttributeMaxDynamicSharedMemorySize, L::SIZE) == cudaSuccess;
        if (attr_ok) cudaOccupancyMaxActiveBlocksPerMultiprocessor(&occ, fused_decode_kernel, NTHREADS, L::SIZE);
        mode = (enc != nullptr && attr_ok && sms * occ >= G) ? 1 : 0;
        (void)cudaGetLastError();
    }
    if (mode == 1) {
        Params p;
        for (int b = 0; b < 2; b++) {
            p.x[b] = (const __nv_bfloat16*)d_in[5 * b + 0];
            encode_kv(enc, &p.km[b], d_in[5 * b + 1]);
            encode_kv(enc, &p.vm[b], d_in[5 * b + 2]);
            encode_wq(enc, &p.wqm[b], d_in[5 * b + 3]);
            p.wo[b] = (const __nv_bfloat16*)d_in[5 * b + 4];
        }
        p.out = (__nv_bfloat16*)d_out;
        fused_decode_kernel<<<G, NTHREADS, L::SIZE>>>(p);
    } else {
        for (int b = 0; b < 2; b++) {
            fb_q_kernel<<<16, 256>>>((const __nv_bfloat16*)d_in[5 * b], (const __nv_bfloat16*)d_in[5 * b + 3], b);
            fb_attn_kernel<<<dim3(FB_SPLIT, 8), 256>>>((const uint4*)d_in[5 * b + 1], (const uint4*)d_in[5 * b + 2], b);
        }
        fb_merge_kernel<<<32, 256>>>();
        for (int b = 0; b < 2; b++)
            fb_out_kernel<<<7, 64>>>((const __nv_bfloat16*)d_in[5 * b + 4], (__nv_bfloat16*)d_out, b);
    }
}
```

```cpp
#include <cuda_runtime.h>
#include <cuda_bf16.h>
#include <cuda.h>
#include <stdint.h>

namespace {

constexpr int G = 132;
constexpr int W = 4;
constexpr int NTHREADS = (W + 2) * 32;
constexpr int TILE_BYTES = 8192;
constexpr int STAGE_BYTES = 2 * TILE_BYTES;
constexpr int TOTAL = 65536;
constexpr int DM = 448;
constexpr int SEG_BYTES = 8 * DM * 2;
constexpr int SLOT_STRIDE = 320;
constexpr int PROG_END = 1 << 30;
constexpr int NS = 12;
constexpr int K0 = 2;
constexpr int Q_DELAY = 1500;
constexpr int MERGE_DELAY = 2500;
constexpr int CAP = 4, CAP_END = 3;
constexpr int END_ZONE = 1000;
constexpr unsigned SPIN_LIMIT = 1u << 22;

struct Params {
    const __nv_bfloat16* x[2];
    __nv_bfloat16* out;
    CUtensorMap km[2];
    CUtensorMap vm[2];
    CUtensorMap wqm[2];
    CUtensorMap wom[2];
};

typedef unsigned long long u64;

__device__ unsigned int g_epoch;
__device__ unsigned int g_ticket;
__device__ ulonglong2 g_q[16 * 2 * 16 * 4];
__device__ uint4 g_po[16 * 32 * G * 4];
__device__ ulonglong2 g_pml[16 * G * 2 * 2];
__device__ uint4 g_ol[2 * 56 * 64 * 2];

#define STAMP(i)

__device__ __forceinline__ uint32_t smem_u32(const void* p) { return (uint32_t)__cvta_generic_to_shared(p); }
__device__ __forceinline__ void mbar_init(uint32_t bar, uint32_t cnt) {
    asm volatile("mbarrier.init.shared::cta.b64 [%0], %1;" ::"r"(bar), "r"(cnt) : "memory");
}
__device__ __forceinline__ void mbar_expect_tx(uint32_t bar, uint32_t bytes) {
    asm volatile("mbarrier.arrive.expect_tx.shared::cta.b64 _, [%0], %1;" ::"r"(bar), "r"(bytes) : "memory");
}
__device__ __forceinline__ void mbar_arrive(uint32_t bar) {
    asm volatile("mbarrier.arrive.shared::cta.b64 _, [%0];" ::"r"(bar) : "memory");
}
__device__ __forceinline__ bool mbar_try(uint32_t bar, uint32_t parity) {
    uint32_t ok;
    asm volatile("{\n.reg .pred p;\nmbarrier.try_wait.parity.shared::cta.b64 p, [%1], %2;\nselp.u32 %0, 1, 0, p;\n}"
                 : "=r"(ok) : "r"(bar), "r"(parity) : "memory");
    return ok != 0;
}
__device__ __forceinline__ void mbar_wait(uint32_t bar, uint32_t parity) {
    unsigned n = 0;
    while (!mbar_try(bar, parity)) {
        if (++n > SPIN_LIMIT) __trap();
    }
}
__device__ __forceinline__ void tma3d(uint32_t dst, const CUtensorMap* m, int row, uint32_t bar, uint64_t pol) {
    asm volatile(
        "cp.async.bulk.tensor.3d.shared::cluster.global.mbarrier::complete_tx::bytes.L2::cache_hint "
        "[%0], [%1, {%3, %4, %3}], [%2], %5;" ::"r"(dst), "l"(m), "r"(bar), "r"(0), "r"(row), "l"(pol)
        : "memory");
}
__device__ __forceinline__ uint64_t evict_first_policy() {
    uint64_t pol;
    asm volatile("createpolicy.fractional.L2::evict_first.b64 %0, 1.0;" : "=l"(pol));
    return pol;
}
__device__ __forceinline__ void ldsm4(uint32_t (&r)[4], uint32_t addr) {
    asm volatile("ldmatrix.sync.aligned.m8n8.x4.shared.b16 {%0,%1,%2,%3}, [%4];"
                 : "=r"(r[0]), "=r"(r[1]), "=r"(r[2]), "=r"(r[3]) : "r"(addr) : "memory");
}
__device__ __forceinline__ void ldsm4t(uint32_t (&r)[4], uint32_t addr) {
    asm volatile("ldmatrix.sync.aligned.m8n8.x4.trans.shared.b16 {%0,%1,%2,%3}, [%4];"
                 : "=r"(r[0]), "=r"(r[1]), "=r"(r[2]), "=r"(r[3]) : "r"(addr) : "memory");
}
__device__ __forceinline__ void mma16816(float (&c)[4], const uint32_t (&a)[4], uint32_t b0, uint32_t b1) {
    asm volatile("mma.sync.aligned.m16n8k16.row.col.f32.bf16.bf16.f32 {%0,%1,%2,%3}, {%4,%5,%6,%7}, {%8,%9}, {%0,%1,%2,%3};"
                 : "+f"(c[0]), "+f"(c[1]), "+f"(c[2]), "+f"(c[3])
                 : "r"(a[0]), "r"(a[1]), "r"(a[2]), "r"(a[3]), "r"(b0), "r"(b1));
}
__device__ __forceinline__ uint32_t movtrans(uint32_t a) {
    uint32_t d;
    asm volatile("movmatrix.sync.aligned.m8n8.trans.b16 %0, %1;" : "=r"(d) : "r"(a));
    return d;
}
__device__ __forceinline__ float ex2(float x) {
    float y;
    asm("ex2.approx.ftz.f32 %0, %1;" : "=f"(y) : "f"(x));
    return y;
}
__device__ __forceinline__ uint32_t pack_bf16(float lo, float hi) {
    uint32_t d;
    asm("cvt.rn.bf16x2.f32 %0, %1, %2;" : "=r"(d) : "f"(hi), "f"(lo));
    return d;
}
__device__ __forceinline__ float bf_lo(uint32_t v) { return __uint_as_float(v << 16); }
__device__ __forceinline__ float bf_hi(uint32_t v) { return __uint_as_float(v & 0xffff0000u); }
__device__ __forceinline__ float warp_max(float v) {
    int k = __float_as_int(v);
    k ^= (k >> 31) & 0x7fffffff;
    k = __reduce_max_sync(0xffffffffu, k);
    k ^= (k >> 31) & 0x7fffffff;
    return __int_as_float(k);
}

__device__ __forceinline__ u64 ll_word(uint32_t v, uint32_t tag) { return ((u64)tag << 32) | v; }
__device__ __forceinline__ void ll_store(ulonglong2* p, uint32_t a, uint32_t b, uint32_t tag) {
    asm volatile("st.relaxed.gpu.global.v2.b64 [%0], {%1, %2};" ::"l"(p), "l"(ll_word(a, tag)), "l"(ll_word(b, tag)) : "memory");
}
__device__ __forceinline__ bool ll_ok(u64 x, u64 y, uint32_t tag) {
    return ((uint32_t)(x >> 32) == tag) & ((uint32_t)(y >> 32) == tag);
}
__device__ __forceinline__ uint32_t pt_enc(float v, uint32_t bit) { return (__float_as_uint(v) & ~1u) | bit; }
__device__ __forceinline__ uint32_t xor_or(uint32_t a, uint32_t b, uint32_t m) {
    uint32_t d;
    asm("lop3.b32 %0, %1, %2, %3, 0x7e;" : "=r"(d) : "r"(a), "r"(b), "r"(m));
    return d;
}
__device__ __forceinline__ uint32_t or3(uint32_t a, uint32_t b, uint32_t c) {
    uint32_t d;
    asm("lop3.b32 %0, %1, %2, %3, 0xfe;" : "=r"(d) : "r"(a), "r"(b), "r"(c));
    return d;
}
__device__ __forceinline__ void st128(uint4* p, uint32_t a, uint32_t b, uint32_t c, uint32_t d) {
    asm volatile("{\n.reg .b128 t;\n.reg .b64 lo, hi;\nmov.b64 lo, {%1, %2};\nmov.b64 hi, {%3, %4};\nmov.b128 t, {lo, hi};\n"
                 "st.relaxed.gpu.global.b128 [%0], t;\n}" ::"l"(p), "r"(a), "r"(b), "r"(c), "r"(d) : "memory");
}
__device__ __forceinline__ void ld128(uint4& v, const uint4* p) {
    asm volatile("{\n.reg .b128 t;\n.reg .b64 lo, hi;\nld.relaxed.gpu.global.b128 t, [%4];\nmov.b128 {lo, hi}, t;\n"
                 "mov.b64 {%0, %1}, lo;\nmov.b64 {%2, %3}, hi;\n}"
                 : "=r"(v.x), "=r"(v.y), "=r"(v.z), "=r"(v.w) : "l"(p) : "memory");
}
__device__ __forceinline__ void ld128_stale(uint4& v, const uint4* p, uint32_t bit) {
    asm volatile("{\n.reg .pred p;\n.reg .b32 u;\n.reg .b128 t;\n.reg .b64 lo, hi;\nand.b32 u, %0, 1;\nsetp.ne.u32 p, u, %5;\n"
                 "mov.b64 lo, {%0, %1};\nmov.b64 hi, {%2, %3};\nmov.b128 t, {lo, hi};\n"
                 "@p ld.relaxed.gpu.global.b128 t, [%4];\nmov.b128 {lo, hi}, t;\nmov.b64 {%0, %1}, lo;\nmov.b64 {%2, %3}, hi;\n}"
                 : "+r"(v.x), "+r"(v.y), "+r"(v.z), "+r"(v.w) : "l"(p), "r"(bit) : "memory");
}
__device__ __forceinline__ void st64(void* p, uint32_t a, uint32_t b) {
    asm volatile("{\n.reg .b64 t;\nmov.b64 t, {%1, %2};\nst.relaxed.gpu.global.b64 [%0], t;\n}" ::"l"(p), "r"(a), "r"(b) : "memory");
}
__device__ __forceinline__ void ld2x64(uint4& v, const uint4* p) {
    asm volatile("{\n.reg .b64 lo, hi;\nld.relaxed.gpu.global.v2.b64 {lo, hi}, [%4];\nmov.b64 {%0, %1}, lo;\nmov.b64 {%2, %3}, hi;\n}"
                 : "=r"(v.x), "=r"(v.y), "=r"(v.z), "=r"(v.w) : "l"(p) : "memory");
}
__device__ __forceinline__ void ldu64(u64& v, const void* p) {
    asm volatile("ld.relaxed.gpu.global.b64 %0, [%1];" : "=l"(v) : "l"(p) : "memory");
}
__device__ __forceinline__ void ldu64_stale(u64& v, const void* p, uint32_t bit) {
    asm volatile("{\n.reg .pred p;\n.reg .b32 a, b;\nmov.b64 {a, b}, %0;\nand.b32 b, b, 1;\nsetp.ne.u32 p, b, %2;\n"
                 "@p ld.relaxed.gpu.global.b64 %0, [%1];\n}" : "+l"(v) : "l"(p), "r"(bit) : "memory");
}
__device__ __forceinline__ void mma1688(float (&c)[4], uint32_t a0, uint32_t a1, uint32_t b0) {
    asm volatile("mma.sync.aligned.m16n8k8.row.col.f32.bf16.bf16.f32 {%0,%1,%2,%3}, {%4,%5}, {%6}, {%0,%1,%2,%3};"
                 : "+f"(c[0]), "+f"(c[1]), "+f"(c[2]), "+f"(c[3]) : "r"(a0), "r"(a1), "r"(b0));
}
__device__ __forceinline__ bool ll_load(const ulonglong2* p, uint32_t& a, uint32_t& b, uint32_t tag) {
    u64 x, y;
    asm volatile("ld.relaxed.gpu.global.v2.b64 {%0, %1}, [%2];" : "=l"(x), "=l"(y) : "l"(p) : "memory");
    a = (uint32_t)x;
    b = (uint32_t)y;
    return ll_ok(x, y, tag);
}

__device__ __forceinline__ void load_wo_frags(uint32_t (&wf)[14][4], uint32_t seg, int lane) {
    const uint32_t row = 4 * ((lane >> 1) & 1) + 2 * ((lane >> 2) & 1) + (lane & 1);
    const uint32_t a = seg + row * 128 + ((((uint32_t)lane >> 3) ^ row) << 4);
#pragma unroll
    for (int x = 0; x < 14; x++) ldsm4t(wf[x], (a ^ ((x & 1) << 6)) + (x >> 1) * 1024);
}
__device__ __forceinline__ void project(float (&y)[7][4], const uint32_t (&wf)[14][4], uint32_t o2, int lane) {
#pragma unroll
    for (int q = 0; q < 4; q++) {
        const uint32_t bq = ((lane >> 2) == 2 * q) ? o2 : 0u;
#pragma unroll
        for (int j = 0; j < 7; j++) {
            const int i = 4 * j + q;
            mma1688(y[j], wf[i >> 1][2 * (i & 1)], wf[i >> 1][2 * (i & 1) + 1], bq);
        }
    }
}

struct L {
    static constexpr int RING = 0;
    static constexpr int SEG = NS * STAGE_BYTES;
    static constexpr int SLOTS = SEG + SEG_BYTES;
    static constexpr int Q0 = SLOTS + W * 2 * SLOT_STRIDE * 4;
    static constexpr int SLOTML = Q0 + 16 * 128 * 8;
    static constexpr int OFIN = SLOTML + W * 16;
    static constexpr int TK = OFIN + 32 * 4;
    static constexpr int BARS = TK + 32 * 4;
    static constexpr int NBARS = 3 * NS + 6 + 8;
    static constexpr int SIZE = BARS + NBARS * 8;
};

__global__ void __launch_bounds__(NTHREADS, 1) fused_decode_kernel(const __grid_constant__ Params p) {
    extern __shared__ __align__(1024) unsigned char smem_raw[];
    static_assert(NS % W == 0 && K0 >= 2 && K0 <= NS - 4 && W == 4, "geometry");
    unsigned char* smem = smem_raw;
    const uint32_t sbase = smem_u32(smem);
    const int warp = threadIdx.x >> 5, lane = threadIdx.x & 31;
    const int cta = blockIdx.x;
    const bool has_task = cta < 128;
    const bool isX = has_task && cta >= 64, isY = cta < 64;
    const int slice = cta & 63;

    const uint32_t bar_full = sbase + L::BARS;
    const uint32_t bar_fullv = bar_full + NS * 8;
    const uint32_t bar_empty = bar_fullv + NS * 8;
    const uint32_t bar_wq = bar_empty + NS * 8;
    const uint32_t bar_q = bar_wq + 8;
    const uint32_t bar_q2 = bar_q + 8;
    const uint32_t bar_q3 = bar_q2 + 8;
    const uint32_t bar_ofin = bar_q3 + 8;
    const uint32_t bar_wo = bar_ofin + 8;
    const uint32_t bar_wqdone = bar_wo + 64;
    volatile int* s_tk = reinterpret_cast<volatile int*>(smem + L::TK);
    float* s_slots = reinterpret_cast<float*>(smem + L::SLOTS);
    float* s_slotml = reinterpret_cast<float*>(smem + L::SLOTML);
    float* s_red = reinterpret_cast<float*>(smem + L::SEG);
    uint32_t* s_ofin = reinterpret_cast<uint32_t*>(smem + L::OFIN);
    uint2* s_q0 = reinterpret_cast<uint2*>(smem + L::Q0);

    uint64_t pol = 0;
    auto issue = [&](int s, int t) {
        s_tk[s] = t;
        s_tk[30] = t;
        const uint32_t dst = sbase + L::RING + s * STAGE_BYTES;
        const int b = t >> 15, row = (t & 32767) << 4;
        mbar_expect_tx(bar_full + s * 8, TILE_BYTES);
        tma3d(dst, &p.km[b], row, bar_full + s * 8, pol);
        mbar_expect_tx(bar_fullv + s * 8, TILE_BYTES);
        tma3d(dst + TILE_BYTES, &p.vm[b], row, bar_fullv + s * 8, pol);
    };
    if (threadIdx.x == W * 32) {
        STAMP(0);
        mbar_init(bar_wq, 1);
#pragma unroll
        for (int i = 0; i < K0; i++) { mbar_init(bar_full + i * 8, 1); mbar_init(bar_fullv + i * 8, 1); }
        asm volatile("fence.mbarrier_init.release.cluster;" ::: "memory");
        pol = evict_first_policy();
        if (has_task) {
            mbar_expect_tx(bar_wq, 448 * 128);
#pragma unroll
            for (int i = 0; i < 2; i++)
                asm volatile(
                    "cp.async.bulk.tensor.2d.shared::cluster.global.mbarrier::complete_tx::bytes.L2::cache_hint "
                    "[%0], [%1, {%3, %4}], [%2], %5;" ::"r"(sbase + L::RING + (NS - 4) * STAGE_BYTES + i * 224 * 128),
                    "l"(&p.wqm[cta >> 6]), "r"(bar_wq), "r"((cta & 63) * 64), "r"(i * 224), "l"(pol) : "memory");
        }
#pragma unroll
        for (int i = 0; i < K0; i++) issue(i, cta + G * i);
#pragma unroll
        for (int i = 0; i < L::NBARS; i++)
            if (!(i < K0 || (i >= NS && i < NS + K0) || i == 3 * NS)) mbar_init(bar_full + i * 8, i == L::NBARS - 1 ? W : 1);
        asm volatile("fence.mbarrier_init.release.cluster;" ::: "memory");
    }

    if (warp == W) {
        __syncwarp();
        asm volatile("bar.arrive 2, %0;" ::"n"(NTHREADS) : "memory");
        if (lane == 0) {
            STAMP(1);
            asm volatile("prefetch.tensormap [%0];" ::"l"(&p.km[1]) : "memory");
            asm volatile("prefetch.tensormap [%0];" ::"l"(&p.vm[1]) : "memory");
            asm volatile("prefetch.tensormap [%0];" ::"l"(&p.wom[0]) : "memory");
        }
        pol = evict_first_policy();
        int s = K0, cnt = K0, t = 0;
        uint32_t ph = 1;
        bool first_lap = has_task;
        while (true) {
            const int cap = (t >= TOTAL - END_ZONE) ? CAP_END : CAP;
            if (cnt >= cap) {
                int sd = s - cap;
                uint32_t pd = ph ^ 1;
                if (sd < 0) { sd += NS; pd ^= 1; }
                mbar_wait(bar_full + sd * 8, pd);
            }
            cnt++;
            unsigned v = 0;
            if (lane == 0) asm volatile("atom.relaxed.gpu.global.inc.u32 %0, [%1], 0x7fffffff;" : "=r"(v) : "l"(&g_ticket) : "memory");
            mbar_wait(bar_empty + s * 8, ph);
            if (first_lap && s == NS - 4) { mbar_wait(bar_wqdone, 0); first_lap = false; }
            t = (int)__shfl_sync(0xffffffffu, v, 0) + G * K0;
            if (t >= TOTAL) break;
            const uint32_t dst = sbase + L::RING + s * STAGE_BYTES;
            const int b = t >> 15;
            asm volatile(
                "{\n.reg .pred p;\nelect.sync _|p, 0xffffffff;\n"
                "@p st.volatile.shared.u32 [%8], %9;\n"
                "@p st.volatile.shared.u32 [%10], %9;\n"
                "@p mbarrier.arrive.expect_tx.shared::cta.b64 _, [%3], 8192;\n"
                "@p cp.async.bulk.tensor.3d.shared::cluster.global.mbarrier::complete_tx::bytes.L2::cache_hint "
                "[%0], [%1, {%5, %6, %5}], [%3], %7;\n"
                "@p mbarrier.arrive.expect_tx.shared::cta.b64 _, [%4], 8192;\n"
                "@p cp.async.bulk.tensor.3d.shared::cluster.global.mbarrier::complete_tx::bytes.L2::cache_hint "
                "[%11], [%2, {%5, %6, %5}], [%4], %7;\n}"
                ::"r"(dst), "l"(&p.km[b]), "l"(&p.vm[b]), "r"(bar_full + s * 8), "r"(bar_fullv + s * 8), "r"(0),
                  "r"((t & 32767) << 4), "l"(pol), "r"(sbase + L::TK + s * 4), "r"(t), "r"(sbase + L::TK + 30 * 4),
                  "r"(dst + TILE_BYTES) : "memory");
            if (++s == NS) { s = 0; ph ^= 1; }
        }
        if (lane == 0) {
            STAMP(2);
            s_tk[30] = PROG_END;
            s_tk[31] = s;
        }
        __syncwarp();
        if (lane < W) {
            int sj = s + lane;
            uint32_t pj = ph;
            if (sj >= NS) { sj -= NS; pj ^= 1; }
            mbar_wait(bar_empty + sj * 8, pj);
            s_tk[sj] = TOTAL;
            mbar_arrive(bar_full + sj * 8);
        }
        __syncwarp();
        if (isY) {
            mbar_wait(bar_wqdone, 0);
            {
                int sd = s - 2;
                uint32_t pd = ph ^ 1;
                if (sd < 0) { sd += NS; pd ^= 1; }
                mbar_wait(bar_full + sd * 8, pd);
            }
            if (lane == 0) STAMP(9);
#pragma unroll
            for (int k = 0; k < 8; k++) {
                int ws = s + (k >> 1);
                if (ws >= NS) ws -= NS;
                asm volatile(
                    "{\n.reg .pred p;\nelect.sync _|p, 0xffffffff;\n"
                    "@p mbarrier.arrive.expect_tx.shared::cta.b64 _, [%2], 7168;\n"
                    "@p cp.async.bulk.tensor.3d.shared::cluster.global.mbarrier::complete_tx::bytes.L2::cache_hint "
                    "[%0], [%1, {%3, %4, %3}], [%2], %5;\n}"
                    ::"r"(sbase + L::RING + ws * STAGE_BYTES + (k & 1) * SEG_BYTES), "l"(&p.wom[0]), "r"(bar_wo + k * 8),
                      "r"(0), "r"(k * 512 + slice * 8), "l"(pol) : "memory");
            }
        }
    } else if (warp == W + 1) {
        uint32_t tag;
        asm volatile("ld.relaxed.gpu.global.u32 %0, [%1];" : "=r"(tag) : "l"(&g_epoch) : "memory");
        tag += 1;
        auto wait_progress = [&](int target) {
            unsigned n = 0;
            while (s_tk[30] < target) {
                __nanosleep(100);
                if (++n > SPIN_LIMIT) __trap();
            }
        };
        {
            bool synced = false;
#pragma unroll 1
            for (int h = 0; h < 16; h++) {
                if (h == 1) wait_progress(Q_DELAY);
                unsigned n = 0;
                uint32_t qa[4], qb[4];
                while (true) {
                    bool ok = true;
#pragma unroll
                    for (int i = 0; i < 4; i++) ok &= ll_load(g_q + h * 128 + i * 32 + lane, qa[i], qb[i], tag);
                    if (!synced) {
                        asm volatile("bar.sync 2, %0;" ::"n"(NTHREADS) : "memory");
                        if (has_task) mbar_wait(bar_wqdone, 0);
                        synced = true;
                    }
                    if (__all_sync(0xffffffffu, ok)) break;
                    if (++n > SPIN_LIMIT) __trap();
                }
#pragma unroll
                for (int i = 0; i < 4; i++) s_q0[h * 128 + i * 32 + lane] = make_uint2(qa[i], qb[i]);
                __syncwarp();
                if (lane == 0) {
                    if (h == 0) mbar_arrive(bar_q);
                    if (h == 3) mbar_arrive(bar_q2);
                    if (h == 15) mbar_arrive(bar_q3);
                }
            }
        }
        if (has_task) {
            const uint32_t bit = tag & 1u, bitmask = 0u - bit;
            const int qh = slice >> 5;
            const int g = lane >> 2, t4 = lane & 3;
            pol = evict_first_policy();
            float y[7][4];
#pragma unroll
            for (int j = 0; j < 7; j++) { y[j][0] = 0.f; y[j][1] = 0.f; y[j][2] = 0.f; y[j][3] = 0.f; }
            const int h0 = isX ? 8 : 0;
#pragma unroll 1
            for (int h = h0; h < h0 + 8; h++) {
                {
                    uint32_t wf[14][4];
                    if (isX) {
                        wait_progress(h * 4096);
                        if (lane == 0) {
                            asm volatile("fence.proxy.async.shared::cta;" ::: "memory");
                            mbar_expect_tx(bar_wo + (h & 7) * 8, SEG_BYTES);
                            tma3d(sbase + L::SEG, &p.wom[1], (h & 7) * 512 + slice * 8, bar_wo + (h & 7) * 8, pol);
                        }
                        mbar_wait(bar_wo + (h & 7) * 8, 0);
                        load_wo_frags(wf, sbase + L::SEG, lane);
                        __syncwarp();
                    }
                    wait_progress(h < 15 ? (h + 1) * 4096 + MERGE_DELAY : PROG_END);
                    u64 ml[5];
                    uint4 ov[9];
                    const ulonglong2* pml = g_pml + ((h * G + lane) * 2 + qh) * 2;
                    const uint4* pr = g_po + ((size_t)(h * 32 + (slice >> 1)) * G + (lane >> 1)) * 4 + (slice & 1) * 2 + (lane & 1);
                    constexpr int PRS = 16 * 4;
                    const ulonglong2* pml4 = pml + (lane < G - 128 ? 4 * 128 : 0);
                    const uint4* pr8 = pr + (lane < (G - 128) * 2 ? 8 * PRS : 0);
#pragma unroll
                    for (int j = 0; j < 5; j++) ldu64(ml[j], j < 4 ? pml + j * 128 : pml4);
#pragma unroll
                    for (int it = 0; it < 9; it++) ld128(ov[it], it < 8 ? pr + it * PRS : pr8);
                    unsigned n = 0;
                    while (true) {
                        const uint32_t bad = or3(
                            or3(xor_or((uint32_t)(ml[0] >> 32), (uint32_t)(ml[1] >> 32), bitmask),
                                xor_or((uint32_t)(ml[2] >> 32), (uint32_t)(ml[3] >> 32), bitmask),
                                xor_or((uint32_t)(ml[4] >> 32), ov[0].x, bitmask)),
                            or3(xor_or(ov[1].x, ov[2].x, bitmask), xor_or(ov[3].x, ov[4].x, bitmask), xor_or(ov[5].x, ov[6].x, bitmask)),
                            xor_or(ov[7].x, ov[8].x, bitmask));
                        if (__all_sync(0xffffffffu, (bad & 1u) == 0) && (h == 15 || n > 0)) break;
                        if (h != 15) __nanosleep(400);
                        if (++n > SPIN_LIMIT) __trap();
#pragma unroll
                        for (int j = 0; j < 5; j++) ldu64_stale(ml[j], j < 4 ? pml + j * 128 : pml4, bit);
#pragma unroll
                        for (int it = 0; it < 9; it++) ld128_stale(ov[it], it < 8 ? pr + it * PRS : pr8, bit);
                    }
                    if (lane == 0) STAMP(32 + h);
                    float mj[5];
#pragma unroll
                    for (int j = 0; j < 5; j++) mj[j] = __uint_as_float((uint32_t)ml[j]);
                    const float M = warp_max(fmaxf(fmaxf(fmaxf(mj[0], mj[1]), fmaxf(mj[2], mj[3])), mj[4]));
                    float wc[5], Ls = 0.f;
#pragma unroll
                    for (int j = 0; j < 5; j++) {
                        wc[j] = ex2(mj[j] - M);
                        if (j == 4 && lane >= G - 128) wc[j] = 0.f;
                        Ls += wc[j] * __uint_as_float((uint32_t)(ml[j] >> 32));
                    }
                    float a0 = 0.f, a1 = 0.f, a2 = 0.f, a3 = 0.f;
#pragma unroll
                    for (int it = 0; it < 9; it++) {
                        const float wv = __shfl_sync(0xffffffffu, wc[it >> 1], 16 * (it & 1) + (lane >> 1));
                        a0 += wv * __uint_as_float(ov[it].x);
                        a1 += wv * __uint_as_float(ov[it].y);
                        a2 += wv * __uint_as_float(ov[it].z);
                        a3 += wv * __uint_as_float(ov[it].w);
                        if (it == 0) Ls += __shfl_xor_sync(0xffffffffu, Ls, 1);
                    }
                    const bool up = lane & 2;
                    float ax = (up ? a2 : a0) + __shfl_xor_sync(0xffffffffu, up ? a0 : a2, 2);
                    float ay = (up ? a3 : a1) + __shfl_xor_sync(0xffffffffu, up ? a1 : a3, 2);
                    Ls += __shfl_xor_sync(0xffffffffu, Ls, 2);
#pragma unroll
                    for (int o = 4; o <= 16; o <<= 1) {
                        ax += __shfl_xor_sync(0xffffffffu, ax, o);
                        ay += __shfl_xor_sync(0xffffffffu, ay, o);
                        Ls += __shfl_xor_sync(0xffffffffu, Ls, o);
                    }
                    float inv;
                    asm("rcp.approx.ftz.f32 %0, %1;" : "=f"(inv) : "f"(Ls));
                    const uint32_t o2 = pack_bf16(ax * inv, ay * inv);
                    if (isY) {
                        if (lane < 4) s_ofin[h * 4 + lane] = o2;
                        __syncwarp();
                        if (h == 7 && lane == 0) mbar_arrive(bar_ofin);
                    } else {
                        if (lane == 0) STAMP(3);
                        project(y, wf, o2, lane);
                    }
                }
                if (h >= 14) {
                    const uint32_t obit = (h == 15) ? bit : bit ^ 1u;
                    char* dst = reinterpret_cast<char*>(g_ol + ((size_t)(56 + g) * 64 + slice) * 2) + t4 * 8;
#pragma unroll
                    for (int j = 0; j < 7; j++) st64(dst + (size_t)j * 8 * 64 * 32, pt_enc(y[j][0], obit), __float_as_uint(y[j][2]));
                    if (lane == 0) STAMP(4);
                }
            }
            if (cta == 127 && lane == 0) {
                asm volatile("st.relaxed.gpu.global.u32 [%0], %1;" ::"l"(&g_ticket), "r"(0u) : "memory");
                asm volatile("st.relaxed.gpu.global.u32 [%0], %1;" ::"l"(&g_epoch), "r"(tag) : "memory");
            }
        }
    } else {
        uint32_t tag;
        asm volatile("ld.relaxed.gpu.global.u32 %0, [%1];" : "=r"(tag) : "l"(&g_epoch) : "memory");
        const int g = lane >> 2, t4 = lane & 3;
        if (has_task) {
            const int tb = cta >> 6, qs = cta & 63;
            const int r = threadIdx.x >> 3, c8 = threadIdx.x & 7;
            const uint2* xp = reinterpret_cast<const uint2*>(p.x[tb] + 28 * r);
            uint2 xv[7];
#pragma unroll
            for (int i = 0; i < 7; i++)
                asm volatile("ld.global.nc.v2.u32 {%0,%1}, [%2];" : "=r"(xv[i].x), "=r"(xv[i].y) : "l"(xp + i));
            asm volatile("bar.sync 2, %0;" ::"n"(NTHREADS) : "memory");
            mbar_wait(bar_wq, 0);
            const uint4* wv = reinterpret_cast<const uint4*>(smem + L::RING + (NS - 4) * STAGE_BYTES) + 28 * r * 8 + c8;
            float acc[8];
#pragma unroll
            for (int j = 0; j < 8; j++) acc[j] = 0.f;
#pragma unroll
            for (int i = 0; i < 28; i++) {
                const uint32_t xw = (i & 2) ? xv[i >> 2].y : xv[i >> 2].x;
                const float xs = (i & 1) ? bf_hi(xw) : bf_lo(xw);
                const uint4 v = wv[i * 8];
                acc[0] += xs * bf_lo(v.x); acc[1] += xs * bf_hi(v.x);
                acc[2] += xs * bf_lo(v.y); acc[3] += xs * bf_hi(v.y);
                acc[4] += xs * bf_lo(v.z); acc[5] += xs * bf_hi(v.z);
                acc[6] += xs * bf_lo(v.w); acc[7] += xs * bf_hi(v.w);
            }
#pragma unroll
            for (int j = 0; j < 8; j++) {
                acc[j] += __shfl_xor_sync(0xffffffffu, acc[j], 8);
                acc[j] += __shfl_xor_sync(0xffffffffu, acc[j], 16);
            }
            if (lane < 8) {
                float4* d = reinterpret_cast<float4*>(s_red + warp * 64 + lane * 8);
                d[0] = make_float4(acc[0], acc[1], acc[2], acc[3]);
                d[1] = make_float4(acc[4], acc[5], acc[6], acc[7]);
            }
            asm volatile("bar.sync 1, %0;" ::"n"(W * 32) : "memory");
            if (threadIdx.x < 16) {
                const int il = threadIdx.x >> 2;
                float q[4];
#pragma unroll
                for (int k = 0; k < 4; k++) {
                    const int d = 16 * il + 2 * t4 + (k & 1) + 8 * (k >> 1);
                    q[k] = 0.f;
#pragma unroll
                    for (int w = 0; w < W; w++) q[k] += s_red[w * 64 + d];
                }
                ll_store(g_q + ((tb * 16 + (qs >> 2)) * 16 + (qs & 3) * 4 + il) * 4 + t4,
                         pack_bf16(q[0], q[1]), pack_bf16(q[2], q[3]), tag + 1);
            }
            __syncwarp();
            if (lane == 0) mbar_arrive(bar_wqdone);
            if (threadIdx.x == 0) STAMP(6);
        } else {
            asm volatile("bar.sync 2, %0;" ::"n"(NTHREADS) : "memory");
        }
        tag += 1;
        const uint32_t bit = tag & 1u;

        float acc[4][4];
#pragma unroll
        for (int i = 0; i < 4; i++) { acc[i][0] = 0.f; acc[i][1] = 0.f; acc[i][2] = 0.f; acc[i][3] = 0.f; }
        float m0 = -INFINITY, m1 = -INFINITY;
        float lacc[4] = {0.f, 0.f, 0.f, 0.f};
        const uint32_t ones[4] = {0x3f803f80u, 0x3f803f80u, 0x3f803f80u, 0x3f803f80u};
        uint32_t qf[16][2];
        int cur = 0;
        const uint32_t krow = (lane & 7) + 8 * ((lane >> 3) & 1), vrow = (lane & 7) + 8 * (lane >> 4);
        const uint32_t koff = krow * 128 + (((lane >> 4) ^ (krow & 7)) << 4);
        const uint32_t voff = TILE_BYTES + vrow * 128 + ((((lane >> 3) & 1) ^ (vrow & 7)) << 4);
        const float SC = 0.0625f * 1.4426950408889634f;
        char* const ydst = reinterpret_cast<char*>(g_ol + ((size_t)(8 * warp + g) * 64 + slice) * 2) + t4 * 8;
        int s = warp;
        uint32_t ph = 0;
        mbar_wait(bar_q, 0);
#pragma unroll
        for (int i = 0; i < 16; i++) {
            const uint2 v = s_q0[((g & 1) * 16 + i) * 4 + t4];
            qf[i][0] = v.x;
            qf[i][1] = v.y;
        }
        if (threadIdx.x == 0) STAMP(7);
        while (true) {
            mbar_wait(bar_full + s * 8, ph);
            const int t = s_tk[s];
            const int h = t >> 12;
            if (h != cur) {
                while (cur < h) {
                    float* sl = s_slots + warp * 2 * SLOT_STRIDE + 16 * t4 + 8 * (t4 >> 1) + g;
                    if (lane == 0) *reinterpret_cast<float4*>(s_slotml + warp * 4) = make_float4(m0, lacc[0], m1, lacc[1]);
#pragma unroll
                    for (int j = 0; j < 4; j++) {
                        sl[80 * j] = acc[j][0];
                        sl[80 * j + SLOT_STRIDE] = acc[j][1];
                        sl[80 * j + 8] = acc[j][2];
                        sl[80 * j + 8 + SLOT_STRIDE] = acc[j][3];
                    }
                    uint4* po = g_po + ((size_t)(cur * 32 + 8 * warp + (lane >> 2)) * G + cta) * 4 + (lane & 3);
                    ulonglong2* pml = g_pml + ((cur * G + cta) * 2 + (warp >> 1)) * 2 + lane;
                    asm volatile("bar.sync 1, %0;" ::"n"(W * 32) : "memory");
                    if (threadIdx.x == 0) STAMP(16 + cur);
                    float2 mlw[W];
                    float4 sv[W];
                    float M = -INFINITY;
#pragma unroll
                    for (int w = 0; w < W; w++) {
                        mlw[w] = *reinterpret_cast<const float2*>(s_slotml + w * 4 + (warp & 2));
                        sv[w] = *reinterpret_cast<const float4*>(s_slots + (w * 2 + (warp >> 1)) * SLOT_STRIDE + 160 * (warp & 1) + 4 * lane + (lane & 24));
                        M = fmaxf(M, mlw[w].x);
                    }
                    const float R = (M == -INFINITY) ? 0.f : M;
                    float4 o = make_float4(0.f, 0.f, 0.f, 0.f);
                    float Lw = 0.f;
#pragma unroll
                    for (int w = 0; w < W; w++) {
                        const float f = ex2(mlw[w].x - R);
                        Lw += f * mlw[w].y;
                        o.x += f * sv[w].x; o.y += f * sv[w].y; o.z += f * sv[w].z; o.w += f * sv[w].w;
                    }
                    st128(po, pt_enc(o.x, bit), __float_as_uint(o.y), __float_as_uint(o.z), __float_as_uint(o.w));
                    const bool mlwriter = !(warp & 1) && lane < 2;
                    if (mlwriter) ll_store(pml, __float_as_uint(M), __float_as_uint(M), pt_enc(Lw, bit));
                    if (cur == 15 && threadIdx.x == 0) STAMP(13);
                    if (cur == 13) {
                        st128(po + 2 * 32 * G * 4, bit ^ 1u, 0u, 0u, 0u);
                        if (mlwriter) ll_store(pml + 2 * G * 4, 0u, 0u, bit ^ 1u);
                        if (isY) {
                            st64(ydst, bit ^ 1u, 0u);
                            if (warp < 3) st64(ydst + 4 * 8 * 64 * 32, bit ^ 1u, 0u);
                        }
                    }
#pragma unroll
                    for (int i = 0; i < 4; i++) { acc[i][0] = 0.f; acc[i][1] = 0.f; acc[i][2] = 0.f; acc[i][3] = 0.f; }
                    m0 = -INFINITY; m1 = -INFINITY;
                    lacc[0] = 0.f; lacc[1] = 0.f; lacc[2] = 0.f; lacc[3] = 0.f;
                    cur++;
                    asm volatile("bar.sync 1, %0;" ::"n"(W * 32) : "memory");
                }
                if (h >= 16) break;
                mbar_wait(h > 3 ? bar_q3 : bar_q2, 0);
#pragma unroll
                for (int i = 0; i < 16; i++) {
                    const uint2 v = s_q0[h * 128 + ((g & 1) * 16 + i) * 4 + t4];
                    qf[i][0] = v.x;
                    qf[i][1] = v.y;
                }
            }
            const uint32_t stage = sbase + L::RING + s * STAGE_BYTES;
            float sc[4][4];
#pragma unroll
            for (int c = 0; c < 4; c++) { sc[c][0] = 0.f; sc[c][1] = 0.f; sc[c][2] = 0.f; sc[c][3] = 0.f; }
            const uint32_t kb = stage + koff;
#pragma unroll
            for (int i = 0; i < 16; i++) {
                uint32_t a[4];
                ldsm4(a, (kb ^ ((i & 3) << 5)) + (i >> 2) * 2048);
                mma16816(sc[i & 3], a, qf[i][0], qf[i][1]);
            }
            const float s0 = ((sc[0][0] + sc[1][0]) + (sc[2][0] + sc[3][0])) * SC;
            const float s1 = ((sc[0][1] + sc[1][1]) + (sc[2][1] + sc[3][1])) * SC;
            const float s2 = ((sc[0][2] + sc[1][2]) + (sc[2][2] + sc[3][2])) * SC;
            const float s3 = ((sc[0][3] + sc[1][3]) + (sc[2][3] + sc[3][3])) * SC;
            float n0 = fmaxf(s0, s2), n1 = fmaxf(s1, s3);
            if (__any_sync(0xffffffffu, (n0 > m0) | (n1 > m1))) {
                n0 = fmaxf(warp_max(n0), m0);
                n1 = fmaxf(warp_max(n1), m1);
                const float f0 = ex2(m0 - n0), f1 = ex2(m1 - n1);
                m0 = n0; m1 = n1;
                lacc[0] *= f0; lacc[1] *= f1; lacc[2] *= f0; lacc[3] *= f1;
#pragma unroll
                for (int i = 0; i < 4; i++) { acc[i][0] *= f0; acc[i][1] *= f1; acc[i][2] *= f0; acc[i][3] *= f1; }
            }
            const float p0 = ex2(s0 - m0), p1 = ex2(s1 - m1), p2 = ex2(s2 - m0), p3 = ex2(s3 - m1);
            const uint32_t b0 = movtrans(pack_bf16(p0, p1));
            const uint32_t b1 = movtrans(pack_bf16(p2, p3));
            mma16816(lacc, ones, b0, b1);
            mbar_wait(bar_fullv + s * 8, ph);
            const uint32_t vb = stage + voff;
#pragma unroll
            for (int q = 0; q < 4; q++) {
                const uint32_t c0 = ((g >> 1) == q) ? b0 : 0u, c1 = ((g >> 1) == q) ? b1 : 0u;
#pragma unroll
                for (int j = 0; j < 4; j++) {
                    uint32_t a[4];
                    ldsm4t(a, (vb ^ (q << 5)) + j * 2048);
                    mma16816(acc[j], a, c0, c1);
                }
            }
            __syncwarp();
            if (lane == 0) mbar_arrive(bar_empty + s * 8);
            s += W;
            if (s >= NS) { s -= NS; ph ^= 1; }
        }

        if (isY) {
            mbar_wait(bar_ofin, 0);
            float y[7][4];
#pragma unroll
            for (int j = 0; j < 7; j++) { y[j][0] = 0.f; y[j][1] = 0.f; y[j][2] = 0.f; y[j][3] = 0.f; }
            float2* red = reinterpret_cast<float2*>(s_red);
#pragma unroll 1
            for (int k = warp; k < 8; k += W) {
                const uint32_t o2 = s_ofin[k * 4 + t4];
                int ws = s_tk[31] + (k >> 1);
                if (ws >= NS) ws -= NS;
                mbar_wait(bar_wo + k * 8, 0);
                uint32_t wf[14][4];
                load_wo_frags(wf, sbase + L::RING + ws * STAGE_BYTES + (k & 1) * SEG_BYTES, lane);
                project(y, wf, o2, lane);
            }
#pragma unroll
            for (int j = 0; j < 7; j++) red[(warp * 7 + j) * 32 + lane] = make_float2(y[j][0], y[j][2]);
            asm volatile("bar.sync 1, %0;" ::"n"(W * 32) : "memory");
            if (threadIdx.x == 0) STAMP(5);
#pragma unroll
            for (int jj = 0; jj < 2; jj++) {
                const int j = warp + 4 * jj;
                if (j < 7) {
                    float vx = 0.f, vy = 0.f;
#pragma unroll
                    for (int w = 0; w < W; w++) {
                        const float2 v = red[(w * 7 + j) * 32 + lane];
                        vx += v.x;
                        vy += v.y;
                    }
                    st64(ydst + jj * 4 * 8 * 64 * 32, pt_enc(vx, bit), __float_as_uint(vy));
                }
            }
            if (threadIdx.x == 0) STAMP(11);
        }
        if (isX && slice < 56 && !(warp & 1)) {
            const bool fb = warp < 2;
            const uint32_t bitmask = 0u - bit;
            const uint4* src = g_ol + (size_t)((fb ? 56 : 0) + slice) * 64 * 2 + lane;
            const int et = 2 * (lane & 1) + ((lane >> 1) & 1), es = (lane >> 2) & 1;
            const int col = (fb ? DM : 0) + 64 * (slice >> 3) + 16 * et + 8 * es + (slice & 7);
            __nv_bfloat16* dst = p.out + col;
            unsigned n = 0;
            while (true) {
                uint4 v[4];
#pragma unroll
                for (int i = 0; i < 4; i++) ld2x64(v[i], src + i * 32);
                const uint32_t bad = or3(xor_or(v[0].x, v[0].z, bitmask), xor_or(v[1].x, v[1].z, bitmask),
                                         xor_or(v[2].x, v[2].z, bitmask)) | xor_or(v[3].x, v[3].z, bitmask);
                const bool done = __all_sync(0xffffffffu, (bad & 1u) == 0);
                const float a0 = (__uint_as_float(v[0].x) + __uint_as_float(v[1].x)) + (__uint_as_float(v[2].x) + __uint_as_float(v[3].x));
                const float a1 = (__uint_as_float(v[0].y) + __uint_as_float(v[1].y)) + (__uint_as_float(v[2].y) + __uint_as_float(v[3].y));
                const float a2 = (__uint_as_float(v[0].z) + __uint_as_float(v[1].z)) + (__uint_as_float(v[2].z) + __uint_as_float(v[3].z));
                const float a3 = (__uint_as_float(v[0].w) + __uint_as_float(v[1].w)) + (__uint_as_float(v[2].w) + __uint_as_float(v[3].w));
                if (done || n == 0) {
                    const bool u1 = lane & 2, u2 = lane & 4;
                    const float bx = (u1 ? a2 : a0) + __shfl_xor_sync(0xffffffffu, u1 ? a0 : a2, 2);
                    const float by = (u1 ? a3 : a1) + __shfl_xor_sync(0xffffffffu, u1 ? a1 : a3, 2);
                    float c = (u2 ? by : bx) + __shfl_xor_sync(0xffffffffu, u2 ? bx : by, 4);
                    c += __shfl_xor_sync(0xffffffffu, c, 8);
                    c += __shfl_xor_sync(0xffffffffu, c, 16);
                    if (done && lane < 8) *dst = __float2bfloat16(c);
                    if (done) break;
                }
                if (++n > SPIN_LIMIT) __trap();
            }
            if (lane == 0 && !(warp & 1)) STAMP(fb ? 8 : 12);
        }
    }
}

constexpr int FB_SPLIT = 64;
__device__ float g_fq[2 * 4096];
__device__ float g_fp[16 * FB_SPLIT * 8 * 2 * 264];

__global__ void fb_q_kernel(const __nv_bfloat16* x, const __nv_bfloat16* wq, int b) {
    const int n = blockIdx.x * blockDim.x + threadIdx.x;
    float a = 0.f;
    for (int k = 0; k < DM; k++) a += __bfloat162float(x[k]) * __bfloat162float(wq[(size_t)k * 4096 + n]);
    g_fq[b * 4096 + n] = __bfloat162float(__float2bfloat16(a));
}
__global__ void fb_attn_kernel(const uint4* k, const uint4* v, int b) {
    const int hk = blockIdx.y, warp = threadIdx.x >> 5, lane = threadIdx.x & 31;
    float q[2][8], o[2][8], m[2] = {-INFINITY, -INFINITY}, l[2] = {0.f, 0.f};
    for (int h = 0; h < 2; h++)
        for (int j = 0; j < 8; j++) { q[h][j] = g_fq[b * 4096 + (hk * 2 + h) * 256 + lane * 8 + j]; o[h][j] = 0.f; }
    const int n = 65536 / FB_SPLIT / 8;
    const size_t row0 = (size_t)hk * 65536 + (size_t)(blockIdx.x * 8 + warp) * n;
    for (int i = 0; i < n; i++) {
        const uint4 kk = k[(row0 + i) * 32 + lane], vv = v[(row0 + i) * 32 + lane];
        const float kf[8] = {bf_lo(kk.x), bf_hi(kk.x), bf_lo(kk.y), bf_hi(kk.y), bf_lo(kk.z), bf_hi(kk.z), bf_lo(kk.w), bf_hi(kk.w)};
        const float vf[8] = {bf_lo(vv.x), bf_hi(vv.x), bf_lo(vv.y), bf_hi(vv.y), bf_lo(vv.z), bf_hi(vv.z), bf_lo(vv.w), bf_hi(vv.w)};
#pragma unroll
        for (int h = 0; h < 2; h++) {
            float s = 0.f;
#pragma unroll
            for (int j = 0; j < 8; j++) s += q[h][j] * kf[j];
            for (int d = 16; d >= 1; d >>= 1) s += __shfl_xor_sync(0xffffffffu, s, d);
            s *= 0.0625f * 1.4426950408889634f;
            const float mn = fmaxf(m[h], s), f = ex2(m[h] - mn), pr = ex2(s - mn);
            m[h] = mn;
            l[h] = l[h] * f + pr;
#pragma unroll
            for (int j = 0; j < 8; j++) o[h][j] = o[h][j] * f + pr * vf[j];
        }
    }
    for (int h = 0; h < 2; h++) {
        float* d = g_fp + ((((size_t)(b * 8 + hk) * FB_SPLIT + blockIdx.x) * 8 + warp) * 2 + h) * 264;
        for (int j = 0; j < 8; j++) d[lane * 8 + j] = o[h][j];
        if (lane == 0) { d[256] = m[h]; d[257] = l[h]; }
    }
}
__global__ void fb_merge_kernel() {
    const int hq = blockIdx.x;
    const float* base = g_fp + ((size_t)(hq >> 1) * FB_SPLIT * 8 * 2 + (hq & 1)) * 264;
    float M = -INFINITY, Ls = 0.f, a = 0.f;
    for (int i = 0; i < FB_SPLIT * 8; i++) M = fmaxf(M, base[(size_t)i * 528 + 256]);
    for (int i = 0; i < FB_SPLIT * 8; i++) {
        const float w = ex2(base[(size_t)i * 528 + 256] - M);
        Ls += w * base[(size_t)i * 528 + 257];
        a += w * base[(size_t)i * 528 + threadIdx.x];
    }
    g_fq[hq * 256 + threadIdx.x] = __bfloat162float(__float2bfloat16(a / Ls));
}
__global__ void fb_out_kernel(const __nv_bfloat16* wo, __nv_bfloat16* out, int b) {
    const int n = blockIdx.x * 64 + threadIdx.x;
    float a = 0.f;
    for (int k = 0; k < 4096; k++) a += g_fq[b * 4096 + k] * __bfloat162float(wo[(size_t)k * DM + n]);
    out[b * DM + n] = __float2bfloat16(a);
}

typedef CUresult (*EncodeFn)(CUtensorMap*, CUtensorMapDataType, cuuint32_t, void*, const cuuint64_t*, const cuuint64_t*,
                             const cuuint32_t*, const cuuint32_t*, CUtensorMapInterleave, CUtensorMapSwizzle,
                             CUtensorMapL2promotion, CUtensorMapFloatOOBfill);

void encode_kv(EncodeFn enc, CUtensorMap* m, const void* ptr) {
    cuuint64_t gd[3] = {64, 8ull * 65536ull, 4};
    cuuint64_t gs[2] = {512, 128};
    cuuint32_t box[3] = {64, 16, 4};
    cuuint32_t es[3] = {1, 1, 1};
    enc(m, CU_TENSOR_MAP_DATA_TYPE_BFLOAT16, 3, const_cast<void*>(ptr), gd, gs, box, es, CU_TENSOR_MAP_INTERLEAVE_NONE,
        CU_TENSOR_MAP_SWIZZLE_128B, CU_TENSOR_MAP_L2_PROMOTION_L2_256B, CU_TENSOR_MAP_FLOAT_OOB_FILL_NONE);
}

void encode_wo(EncodeFn enc, CUtensorMap* m, const void* ptr) {
    cuuint64_t gd[3] = {64, 4096, 7};
    cuuint64_t gs[2] = {DM * 2, 128};
    cuuint32_t box[3] = {64, 8, 7};
    cuuint32_t es[3] = {1, 1, 1};
    enc(m, CU_TENSOR_MAP_DATA_TYPE_BFLOAT16, 3, const_cast<void*>(ptr), gd, gs, box, es, CU_TENSOR_MAP_INTERLEAVE_NONE,
        CU_TENSOR_MAP_SWIZZLE_128B, CU_TENSOR_MAP_L2_PROMOTION_L2_128B, CU_TENSOR_MAP_FLOAT_OOB_FILL_NONE);
}

void encode_wq(EncodeFn enc, CUtensorMap* m, const void* ptr) {
    cuuint64_t gd[2] = {4096, 448};
    cuuint64_t gs[1] = {8192};
    cuuint32_t box[2] = {64, 224};
    cuuint32_t es[2] = {1, 1};
    enc(m, CU_TENSOR_MAP_DATA_TYPE_BFLOAT16, 2, const_cast<void*>(ptr), gd, gs, box, es, CU_TENSOR_MAP_INTERLEAVE_NONE,
        CU_TENSOR_MAP_SWIZZLE_NONE, CU_TENSOR_MAP_L2_PROMOTION_L2_128B, CU_TENSOR_MAP_FLOAT_OOB_FILL_NONE);
}

}

extern "C" void kernel_launch(void* const* d_in, const int* in_sizes, int n_in, void* d_out, int out_size) {
    (void)in_sizes; (void)n_in; (void)out_size;
    static EncodeFn enc = nullptr;
    static int mode = -1;
    if (mode < 0) {
        cudaDriverEntryPointQueryResult qr;
        void* fn = nullptr;
        cudaGetDriverEntryPoint("cuTensorMapEncodeTiled", &fn, cudaEnableDefault, &qr);
        enc = (EncodeFn)fn;
        int dev = 0, sms = 0, occ = 0;
        cudaGetDevice(&dev);
        cudaDeviceGetAttribute(&sms, cudaDevAttrMultiProcessorCount, dev);
        const bool attr_ok =
            cudaFuncSetAttribute(fused_decode_kernel, cudaFuncAttributeMaxDynamicSharedMemorySize, L::SIZE) == cudaSuccess;
        if (attr_ok) cudaOccupancyMaxActiveBlocksPerMultiprocessor(&occ, fused_decode_kernel, NTHREADS, L::SIZE);
        mode = (enc != nullptr && attr_ok && sms * occ >= G) ? 1 : 0;
        (void)cudaGetLastError();
    }
    if (mode == 1) {
        Params p;
        for (int b = 0; b < 2; b++) {
            p.x[b] = (const __nv_bfloat16*)d_in[5 * b + 0];
            encode_kv(enc, &p.km[b], d_in[5 * b + 1]);
            encode_kv(enc, &p.vm[b], d_in[5 * b + 2]);
            encode_wq(enc, &p.wqm[b], d_in[5 * b + 3]);
            encode_wo(enc, &p.wom[b], d_in[5 * b + 4]);
        }
        p.out = (__nv_bfloat16*)d_out;
        fused_decode_kernel<<<G, NTHREADS, L::SIZE>>>(p);
    } else {
        for (int b = 0; b < 2; b++) {
            fb_q_kernel<<<16, 256>>>((const __nv_bfloat16*)d_in[5 * b], (const __nv_bfloat16*)d_in[5 * b + 3], b);
            fb_attn_kernel<<<dim3(FB_SPLIT, 8), 256>>>((const uint4*)d_in[5 * b + 1], (const uint4*)d_in[5 * b + 2], b);
        }
        fb_merge_kernel<<<32, 256>>>();
        for (int b = 0; b < 2; b++)
            fb_out_kernel<<<7, 64>>>((const __nv_bfloat16*)d_in[5 * b + 4], (__nv_bfloat16*)d_out, b);
    }
}
```

```cpp
#include <cuda_runtime.h>
#include <cuda_bf16.h>
#include <cuda.h>
#include <stdint.h>

namespace {

constexpr int G = 132;
constexpr int W = 4;
constexpr int NTHREADS = (W + 2) * 32;
constexpr int TILE_BYTES = 8192;
constexpr int STAGE_BYTES = 2 * TILE_BYTES;
constexpr int TOTAL = 65536;
constexpr int DM = 448;
constexpr int SEG_BYTES = 8 * DM * 2;
constexpr int SLOT_STRIDE = 320;
constexpr int PROG_END = 1 << 30;
constexpr int NS = 12;
constexpr int K0 = 2;
constexpr int Q_DELAY = 1500;
constexpr int MERGE_DELAY = 2500;
constexpr int CAP = 4, CAP_END = 3;
constexpr int END_ZONE = 1000;
constexpr unsigned SPIN_LIMIT = 1u << 22;

struct Params {
    const __nv_bfloat16* x[2];
    __nv_bfloat16* out;
    CUtensorMap km[2];
    CUtensorMap vm[2];
    CUtensorMap wqm[2];
    CUtensorMap wom[2];
};

typedef unsigned long long u64;

__device__ unsigned int g_epoch;
__device__ unsigned int g_ticket;
__device__ ulonglong2 g_q[16 * 2 * 16 * 4];
__device__ uint4 g_po[16 * 32 * G * 4];
__device__ ulonglong2 g_pml[16 * G * 2 * 2];
__device__ uint4 g_ol[2 * 56 * 64 * 2];

__device__ __forceinline__ uint32_t smem_u32(const void* p) { return (uint32_t)__cvta_generic_to_shared(p); }
__device__ __forceinline__ void mbar_init(uint32_t bar, uint32_t cnt) {
    asm volatile("mbarrier.init.shared::cta.b64 [%0], %1;" ::"r"(bar), "r"(cnt) : "memory");
}
__device__ __forceinline__ void mbar_expect_tx(uint32_t bar, uint32_t bytes) {
    asm volatile("mbarrier.arrive.expect_tx.shared::cta.b64 _, [%0], %1;" ::"r"(bar), "r"(bytes) : "memory");
}
__device__ __forceinline__ void mbar_arrive(uint32_t bar) {
    asm volatile("mbarrier.arrive.shared::cta.b64 _, [%0];" ::"r"(bar) : "memory");
}
__device__ __forceinline__ bool mbar_try(uint32_t bar, uint32_t parity) {
    uint32_t ok;
    asm volatile("{\n.reg .pred p;\nmbarrier.try_wait.parity.shared::cta.b64 p, [%1], %2;\nselp.u32 %0, 1, 0, p;\n}"
                 : "=r"(ok) : "r"(bar), "r"(parity) : "memory");
    return ok != 0;
}
__device__ __forceinline__ void mbar_wait(uint32_t bar, uint32_t parity) {
    unsigned n = 0;
    while (!mbar_try(bar, parity)) {
        if (++n > SPIN_LIMIT) __trap();
    }
}
__device__ __forceinline__ void tma3d(uint32_t dst, const CUtensorMap* m, int row, uint32_t bar, uint64_t pol) {
    asm volatile(
        "cp.async.bulk.tensor.3d.shared::cluster.global.mbarrier::complete_tx::bytes.L2::cache_hint "
        "[%0], [%1, {%3, %4, %3}], [%2], %5;" ::"r"(dst), "l"(m), "r"(bar), "r"(0), "r"(row), "l"(pol)
        : "memory");
}
__device__ __forceinline__ uint64_t evict_first_policy() {
    uint64_t pol;
    asm volatile("createpolicy.fractional.L2::evict_first.b64 %0, 1.0;" : "=l"(pol));
    return pol;
}
__device__ __forceinline__ void ldsm4(uint32_t (&r)[4], uint32_t addr) {
    asm volatile("ldmatrix.sync.aligned.m8n8.x4.shared.b16 {%0,%1,%2,%3}, [%4];"
                 : "=r"(r[0]), "=r"(r[1]), "=r"(r[2]), "=r"(r[3]) : "r"(addr) : "memory");
}
__device__ __forceinline__ void ldsm4t(uint32_t (&r)[4], uint32_t addr) {
    asm volatile("ldmatrix.sync.aligned.m8n8.x4.trans.shared.b16 {%0,%1,%2,%3}, [%4];"
                 : "=r"(r[0]), "=r"(r[1]), "=r"(r[2]), "=r"(r[3]) : "r"(addr) : "memory");
}
__device__ __forceinline__ void mma16816(float (&c)[4], const uint32_t (&a)[4], uint32_t b0, uint32_t b1) {
    asm volatile("mma.sync.aligned.m16n8k16.row.col.f32.bf16.bf16.f32 {%0,%1,%2,%3}, {%4,%5,%6,%7}, {%8,%9}, {%0,%1,%2,%3};"
                 : "+f"(c[0]), "+f"(c[1]), "+f"(c[2]), "+f"(c[3])
                 : "r"(a[0]), "r"(a[1]), "r"(a[2]), "r"(a[3]), "r"(b0), "r"(b1));
}
__device__ __forceinline__ uint32_t movtrans(uint32_t a) {
    uint32_t d;
    asm volatile("movmatrix.sync.aligned.m8n8.trans.b16 %0, %1;" : "=r"(d) : "r"(a));
    return d;
}
__device__ __forceinline__ float ex2(float x) {
    float y;
    asm("ex2.approx.ftz.f32 %0, %1;" : "=f"(y) : "f"(x));
    return y;
}
__device__ __forceinline__ uint32_t pack_bf16(float lo, float hi) {
    uint32_t d;
    asm("cvt.rn.bf16x2.f32 %0, %1, %2;" : "=r"(d) : "f"(hi), "f"(lo));
    return d;
}
__device__ __forceinline__ float bf_lo(uint32_t v) { return __uint_as_float(v << 16); }
__device__ __forceinline__ float bf_hi(uint32_t v) { return __uint_as_float(v & 0xffff0000u); }
__device__ __forceinline__ float warp_max(float v) {
    int k = __float_as_int(v);
    k ^= (k >> 31) & 0x7fffffff;
    k = __reduce_max_sync(0xffffffffu, k);
    k ^= (k >> 31) & 0x7fffffff;
    return __int_as_float(k);
}

__device__ __forceinline__ uint32_t ticket_base(uint32_t epoch) { return (~epoch & 0x7ffu) << 20; }

__device__ __forceinline__ u64 ll_word(uint32_t v, uint32_t tag) { return ((u64)tag << 32) | v; }
__device__ __forceinline__ void ll_store(ulonglong2* p, uint32_t a, uint32_t b, uint32_t tag) {
    asm volatile("st.relaxed.gpu.global.v2.b64 [%0], {%1, %2};" ::"l"(p), "l"(ll_word(a, tag)), "l"(ll_word(b, tag)) : "memory");
}
__device__ __forceinline__ bool ll_ok(u64 x, u64 y, uint32_t tag) {
    return ((uint32_t)(x >> 32) == tag) & ((uint32_t)(y >> 32) == tag);
}
__device__ __forceinline__ uint32_t pt_enc(float v, uint32_t bit) { return (__float_as_uint(v) & ~1u) | bit; }
__device__ __forceinline__ uint32_t xor_or(uint32_t a, uint32_t b, uint32_t m) {
    uint32_t d;
    asm("lop3.b32 %0, %1, %2, %3, 0x7e;" : "=r"(d) : "r"(a), "r"(b), "r"(m));
    return d;
}
__device__ __forceinline__ uint32_t or3(uint32_t a, uint32_t b, uint32_t c) {
    uint32_t d;
    asm("lop3.b32 %0, %1, %2, %3, 0xfe;" : "=r"(d) : "r"(a), "r"(b), "r"(c));
    return d;
}
__device__ __forceinline__ void st128(uint4* p, uint32_t a, uint32_t b, uint32_t c, uint32_t d) {
    asm volatile("{\n.reg .b128 t;\n.reg .b64 lo, hi;\nmov.b64 lo, {%1, %2};\nmov.b64 hi, {%3, %4};\nmov.b128 t, {lo, hi};\n"
                 "st.relaxed.gpu.global.b128 [%0], t;\n}" ::"l"(p), "r"(a), "r"(b), "r"(c), "r"(d) : "memory");
}
__device__ __forceinline__ void ld128(uint4& v, const uint4* p) {
    asm volatile("{\n.reg .b128 t;\n.reg .b64 lo, hi;\nld.relaxed.gpu.global.b128 t, [%4];\nmov.b128 {lo, hi}, t;\n"
                 "mov.b64 {%0, %1}, lo;\nmov.b64 {%2, %3}, hi;\n}"
                 : "=r"(v.x), "=r"(v.y), "=r"(v.z), "=r"(v.w) : "l"(p) : "memory");
}
__device__ __forceinline__ void ld128_stale(uint4& v, const uint4* p, uint32_t bit) {
    asm volatile("{\n.reg .pred p;\n.reg .b32 u;\n.reg .b128 t;\n.reg .b64 lo, hi;\nand.b32 u, %0, 1;\nsetp.ne.u32 p, u, %5;\n"
                 "mov.b64 lo, {%0, %1};\nmov.b64 hi, {%2, %3};\nmov.b128 t, {lo, hi};\n"
                 "@p ld.relaxed.gpu.global.b128 t, [%4];\nmov.b128 {lo, hi}, t;\nmov.b64 {%0, %1}, lo;\nmov.b64 {%2, %3}, hi;\n}"
                 : "+r"(v.x), "+r"(v.y), "+r"(v.z), "+r"(v.w) : "l"(p), "r"(bit) : "memory");
}
__device__ __forceinline__ void st64(void* p, uint32_t a, uint32_t b) {
    asm volatile("{\n.reg .b64 t;\nmov.b64 t, {%1, %2};\nst.relaxed.gpu.global.b64 [%0], t;\n}" ::"l"(p), "r"(a), "r"(b) : "memory");
}
__device__ __forceinline__ void ld2x64(uint4& v, const uint4* p) {
    asm volatile("{\n.reg .b64 lo, hi;\nld.relaxed.gpu.global.v2.b64 {lo, hi}, [%4];\nmov.b64 {%0, %1}, lo;\nmov.b64 {%2, %3}, hi;\n}"
                 : "=r"(v.x), "=r"(v.y), "=r"(v.z), "=r"(v.w) : "l"(p) : "memory");
}
__device__ __forceinline__ void ldu64(u64& v, const void* p) {
    asm volatile("ld.relaxed.gpu.global.b64 %0, [%1];" : "=l"(v) : "l"(p) : "memory");
}
__device__ __forceinline__ void ldu64_stale(u64& v, const void* p, uint32_t bit) {
    asm volatile("{\n.reg .pred p;\n.reg .b32 a, b;\nmov.b64 {a, b}, %0;\nand.b32 b, b, 1;\nsetp.ne.u32 p, b, %2;\n"
                 "@p ld.relaxed.gpu.global.b64 %0, [%1];\n}" : "+l"(v) : "l"(p), "r"(bit) : "memory");
}
__device__ __forceinline__ void mma1688(float (&c)[4], uint32_t a0, uint32_t a1, uint32_t b0) {
    asm volatile("mma.sync.aligned.m16n8k8.row.col.f32.bf16.bf16.f32 {%0,%1,%2,%3}, {%4,%5}, {%6}, {%0,%1,%2,%3};"
                 : "+f"(c[0]), "+f"(c[1]), "+f"(c[2]), "+f"(c[3]) : "r"(a0), "r"(a1), "r"(b0));
}
__device__ __forceinline__ bool ll_load(const ulonglong2* p, uint32_t& a, uint32_t& b, uint32_t tag) {
    u64 x, y;
    asm volatile("ld.relaxed.gpu.global.v2.b64 {%0, %1}, [%2];" : "=l"(x), "=l"(y) : "l"(p) : "memory");
    a = (uint32_t)x;
    b = (uint32_t)y;
    return ll_ok(x, y, tag);
}

__device__ __forceinline__ void load_wo_frags(uint32_t (&wf)[14][4], uint32_t seg, int lane) {
    const uint32_t row = 4 * ((lane >> 1) & 1) + 2 * ((lane >> 2) & 1) + (lane & 1);
    const uint32_t a = seg + row * 128 + ((((uint32_t)lane >> 3) ^ row) << 4);
#pragma unroll
    for (int x = 0; x < 14; x++) ldsm4t(wf[x], (a ^ ((x & 1) << 6)) + (x >> 1) * 1024);
}
__device__ __forceinline__ void project(float (&y)[7][4], const uint32_t (&wf)[14][4], uint32_t o2, int lane) {
#pragma unroll
    for (int q = 0; q < 4; q++) {
        const uint32_t bq = ((lane >> 2) == 2 * q) ? o2 : 0u;
#pragma unroll
        for (int j = 0; j < 7; j++) {
            const int i = 4 * j + q;
            mma1688(y[j], wf[i >> 1][2 * (i & 1)], wf[i >> 1][2 * (i & 1) + 1], bq);
        }
    }
}

struct L {
    static constexpr int RING = 0;
    static constexpr int SEG = NS * STAGE_BYTES;
    static constexpr int SLOTS = SEG + SEG_BYTES;
    static constexpr int Q0 = SLOTS + W * 2 * SLOT_STRIDE * 4;
    static constexpr int SLOTML = Q0 + 16 * 128 * 8;
    static constexpr int OFIN = SLOTML + W * 16;
    static constexpr int TK = OFIN + 32 * 4;
    static constexpr int BARS = TK + 32 * 4;
    static constexpr int NBARS = 3 * NS + 6 + 8;
    static constexpr int SIZE = BARS + NBARS * 8;
};

__global__ void __launch_bounds__(NTHREADS, 1) fused_decode_kernel(const __grid_constant__ Params p) {
    extern __shared__ __align__(1024) unsigned char smem_raw[];
    static_assert(NS % W == 0 && K0 >= 2 && K0 <= NS - 4 && W == 4, "geometry");
    unsigned char* smem = smem_raw;
    const uint32_t sbase = smem_u32(smem);
    const int warp = threadIdx.x >> 5, lane = threadIdx.x & 31;
    const int cta = blockIdx.x;
    const bool has_task = cta < 128;
    const bool isX = has_task && cta >= 64, isY = cta < 64;
    const int slice = cta & 63;

    const uint32_t bar_full = sbase + L::BARS;
    const uint32_t bar_fullv = bar_full + NS * 8;
    const uint32_t bar_empty = bar_fullv + NS * 8;
    const uint32_t bar_wq = bar_empty + NS * 8;
    const uint32_t bar_q = bar_wq + 8;
    const uint32_t bar_q2 = bar_q + 8;
    const uint32_t bar_q3 = bar_q2 + 8;
    const uint32_t bar_ofin = bar_q3 + 8;
    const uint32_t bar_wo = bar_ofin + 8;
    const uint32_t bar_wqdone = bar_wo + 64;
    volatile int* s_tk = reinterpret_cast<volatile int*>(smem + L::TK);
    float* s_slots = reinterpret_cast<float*>(smem + L::SLOTS);
    float* s_slotml = reinterpret_cast<float*>(smem + L::SLOTML);
    float* s_red = reinterpret_cast<float*>(smem + L::SEG);
    uint32_t* s_ofin = reinterpret_cast<uint32_t*>(smem + L::OFIN);
    uint2* s_q0 = reinterpret_cast<uint2*>(smem + L::Q0);

    uint64_t pol = 0;
    auto issue = [&](int s, int t) {
        s_tk[s] = t;
        s_tk[30] = t;
        const uint32_t dst = sbase + L::RING + s * STAGE_BYTES;
        const int b = t >> 15, row = (t & 32767) << 4;
        mbar_expect_tx(bar_full + s * 8, TILE_BYTES);
        tma3d(dst, &p.km[b], row, bar_full + s * 8, pol);
        mbar_expect_tx(bar_fullv + s * 8, TILE_BYTES);
        tma3d(dst + TILE_BYTES, &p.vm[b], row, bar_fullv + s * 8, pol);
    };
    if (threadIdx.x == W * 32) {
        mbar_init(bar_wq, 1);
#pragma unroll
        for (int i = 0; i < K0; i++) { mbar_init(bar_full + i * 8, 1); mbar_init(bar_fullv + i * 8, 1); }
        asm volatile("fence.mbarrier_init.release.cluster;" ::: "memory");
        pol = evict_first_policy();
        if (has_task) {
            mbar_expect_tx(bar_wq, 448 * 128);
#pragma unroll
            for (int i = 0; i < 2; i++)
                asm volatile(
                    "cp.async.bulk.tensor.2d.shared::cluster.global.mbarrier::complete_tx::bytes.L2::cache_hint "
                    "[%0], [%1, {%3, %4}], [%2], %5;" ::"r"(sbase + L::RING + (NS - 4) * STAGE_BYTES + i * 224 * 128),
                    "l"(&p.wqm[cta >> 6]), "r"(bar_wq), "r"((cta & 63) * 64), "r"(i * 224), "l"(pol) : "memory");
        }
#pragma unroll
        for (int i = 0; i < K0; i++) issue(i, cta + G * i);
#pragma unroll
        for (int i = 0; i < L::NBARS; i++)
            if (!(i < K0 || (i >= NS && i < NS + K0) || i == 3 * NS)) mbar_init(bar_full + i * 8, i == L::NBARS - 1 ? W : 1);
        asm volatile("fence.mbarrier_init.release.cluster;" ::: "memory");
    }

    if (warp == W) {
        __syncwarp();
        asm volatile("bar.arrive 2, %0;" ::"n"(NTHREADS) : "memory");
        if (lane == 0) {
            asm volatile("prefetch.tensormap [%0];" ::"l"(&p.km[1]) : "memory");
            asm volatile("prefetch.tensormap [%0];" ::"l"(&p.vm[1]) : "memory");
            asm volatile("prefetch.tensormap [%0];" ::"l"(&p.wom[0]) : "memory");
        }
        pol = evict_first_policy();
        uint32_t ttag;
        asm volatile("ld.relaxed.gpu.global.u32 %0, [%1];" : "=r"(ttag) : "l"(&g_epoch) : "memory");
        int s = K0, cnt = K0, t = 0;
        uint32_t ph = 1;
        bool first_lap = has_task;
        while (true) {
            const int cap = (t >= TOTAL - END_ZONE) ? CAP_END : CAP;
            if (cnt >= cap) {
                int sd = s - cap;
                uint32_t pd = ph ^ 1;
                if (sd < 0) { sd += NS; pd ^= 1; }
                mbar_wait(bar_full + sd * 8, pd);
            }
            cnt++;
            unsigned v = 0;
            if (lane == 0) asm volatile("atom.relaxed.gpu.global.inc.u32 %0, [%1], 0x7fffffff;" : "=r"(v) : "l"(&g_ticket) : "memory");
            mbar_wait(bar_empty + s * 8, ph);
            if (first_lap && s == NS - 4) { mbar_wait(bar_wqdone, 0); first_lap = false; }
            v = __shfl_sync(0xffffffffu, v, 0) - ticket_base(ttag);
            if (v >= (1u << 20)) {
                unsigned n = 0;
                do {
                    __nanosleep(100);
                    if (lane == 0) asm volatile("atom.relaxed.gpu.global.inc.u32 %0, [%1], 0x7fffffff;" : "=r"(v) : "l"(&g_ticket) : "memory");
                    v = __shfl_sync(0xffffffffu, v, 0) - ticket_base(ttag);
                    if (++n > SPIN_LIMIT) __trap();
                } while (v >= (1u << 20));
            }
            t = (int)v + G * K0;
            if (t >= TOTAL) break;
            const uint32_t dst = sbase + L::RING + s * STAGE_BYTES;
            const int b = t >> 15;
            asm volatile(
                "{\n.reg .pred p;\nelect.sync _|p, 0xffffffff;\n"
                "@p st.volatile.shared.u32 [%8], %9;\n"
                "@p st.volatile.shared.u32 [%10], %9;\n"
                "@p mbarrier.arrive.expect_tx.shared::cta.b64 _, [%3], 8192;\n"
                "@p cp.async.bulk.tensor.3d.shared::cluster.global.mbarrier::complete_tx::bytes.L2::cache_hint "
                "[%0], [%1, {%5, %6, %5}], [%3], %7;\n"
                "@p mbarrier.arrive.expect_tx.shared::cta.b64 _, [%4], 8192;\n"
                "@p cp.async.bulk.tensor.3d.shared::cluster.global.mbarrier::complete_tx::bytes.L2::cache_hint "
                "[%11], [%2, {%5, %6, %5}], [%4], %7;\n}"
                ::"r"(dst), "l"(&p.km[b]), "l"(&p.vm[b]), "r"(bar_full + s * 8), "r"(bar_fullv + s * 8), "r"(0),
                  "r"((t & 32767) << 4), "l"(pol), "r"(sbase + L::TK + s * 4), "r"(t), "r"(sbase + L::TK + 30 * 4),
                  "r"(dst + TILE_BYTES) : "memory");
            if (++s == NS) { s = 0; ph ^= 1; }
        }
        if (lane == 0) {
            s_tk[30] = PROG_END;
            s_tk[31] = s;
        }
        __syncwarp();
        if (lane < W) {
            int sj = s + lane;
            uint32_t pj = ph;
            if (sj >= NS) { sj -= NS; pj ^= 1; }
            mbar_wait(bar_empty + sj * 8, pj);
            s_tk[sj] = TOTAL;
            mbar_arrive(bar_full + sj * 8);
        }
        __syncwarp();
        if (isY) {
            mbar_wait(bar_wqdone, 0);
            {
                int sd = s - 2;
                uint32_t pd = ph ^ 1;
                if (sd < 0) { sd += NS; pd ^= 1; }
                mbar_wait(bar_full + sd * 8, pd);
            }
#pragma unroll
            for (int k = 0; k < 8; k++) {
                int ws = s + (k >> 1);
                if (ws >= NS) ws -= NS;
                asm volatile(
                    "{\n.reg .pred p;\nelect.sync _|p, 0xffffffff;\n"
                    "@p mbarrier.arrive.expect_tx.shared::cta.b64 _, [%2], 7168;\n"
                    "@p cp.async.bulk.tensor.3d.shared::cluster.global.mbarrier::complete_tx::bytes.L2::cache_hint "
                    "[%0], [%1, {%3, %4, %3}], [%2], %5;\n}"
                    ::"r"(sbase + L::RING + ws * STAGE_BYTES + (k & 1) * SEG_BYTES), "l"(&p.wom[0]), "r"(bar_wo + k * 8),
                      "r"(0), "r"(k * 512 + slice * 8), "l"(pol) : "memory");
            }
        }
    } else if (warp == W + 1) {
        uint32_t tag;
        asm volatile("ld.relaxed.gpu.global.u32 %0, [%1];" : "=r"(tag) : "l"(&g_epoch) : "memory");
        if (cta == G - 1 && lane == 0)
            asm volatile("st.relaxed.gpu.global.u32 [%0], %1;" ::"l"(&g_ticket), "r"(ticket_base(tag)) : "memory");
        tag += 1;
        auto wait_progress = [&](int target) {
            unsigned n = 0;
            while (s_tk[30] < target) {
                __nanosleep(100);
                if (++n > SPIN_LIMIT) __trap();
            }
        };
        {
            bool synced = false;
#pragma unroll 1
            for (int h = 0; h < 16; h++) {
                if (h == 1) wait_progress(Q_DELAY);
                unsigned n = 0;
                uint32_t qa[4], qb[4];
                while (true) {
                    bool ok = true;
#pragma unroll
                    for (int i = 0; i < 4; i++) ok &= ll_load(g_q + h * 128 + i * 32 + lane, qa[i], qb[i], tag);
                    if (!synced) {
                        asm volatile("bar.sync 2, %0;" ::"n"(NTHREADS) : "memory");
                        if (has_task) mbar_wait(bar_wqdone, 0);
                        synced = true;
                    }
                    if (__all_sync(0xffffffffu, ok)) break;
                    if (++n > SPIN_LIMIT) __trap();
                }
#pragma unroll
                for (int i = 0; i < 4; i++) s_q0[h * 128 + i * 32 + lane] = make_uint2(qa[i], qb[i]);
                __syncwarp();
                if (lane == 0) {
                    if (h == 0) mbar_arrive(bar_q);
                    if (h == 3) mbar_arrive(bar_q2);
                    if (h == 15) mbar_arrive(bar_q3);
                }
            }
        }
        if (has_task) {
            const uint32_t bit = tag & 1u, bitmask = 0u - bit;
            const int qh = slice >> 5;
            const int g = lane >> 2, t4 = lane & 3;
            pol = evict_first_policy();
            float y[7][4];
#pragma unroll
            for (int j = 0; j < 7; j++) { y[j][0] = 0.f; y[j][1] = 0.f; y[j][2] = 0.f; y[j][3] = 0.f; }
            const int h0 = isX ? 8 : 0;
#pragma unroll 1
            for (int h = h0; h < h0 + 8; h++) {
                {
                    uint32_t wf[14][4];
                    if (isX) {
                        wait_progress(h * 4096);
                        if (lane == 0) {
                            asm volatile("fence.proxy.async.shared::cta;" ::: "memory");
                            mbar_expect_tx(bar_wo + (h & 7) * 8, SEG_BYTES);
                            tma3d(sbase + L::SEG, &p.wom[1], (h & 7) * 512 + slice * 8, bar_wo + (h & 7) * 8, pol);
                        }
                        mbar_wait(bar_wo + (h & 7) * 8, 0);
                        load_wo_frags(wf, sbase + L::SEG, lane);
                        __syncwarp();
                    }
                    wait_progress(h < 15 ? (h + 1) * 4096 + MERGE_DELAY : PROG_END);
                    u64 ml[5];
                    uint4 ov[9];
                    const ulonglong2* pml = g_pml + ((h * G + lane) * 2 + qh) * 2;
                    const uint4* pr = g_po + ((size_t)(h * 32 + (slice >> 1)) * G + (lane >> 1)) * 4 + (slice & 1) * 2 + (lane & 1);
                    constexpr int PRS = 16 * 4;
                    const ulonglong2* pml4 = pml + (lane < G - 128 ? 4 * 128 : 0);
                    const uint4* pr8 = pr + (lane < (G - 128) * 2 ? 8 * PRS : 0);
#pragma unroll
                    for (int j = 0; j < 5; j++) ldu64(ml[j], j < 4 ? pml + j * 128 : pml4);
#pragma unroll
                    for (int it = 0; it < 9; it++) ld128(ov[it], it < 8 ? pr + it * PRS : pr8);
                    unsigned n = 0;
                    while (true) {
                        const uint32_t bad = or3(
                            or3(xor_or((uint32_t)(ml[0] >> 32), (uint32_t)(ml[1] >> 32), bitmask),
                                xor_or((uint32_t)(ml[2] >> 32), (uint32_t)(ml[3] >> 32), bitmask),
                                xor_or((uint32_t)(ml[4] >> 32), ov[0].x, bitmask)),
                            or3(xor_or(ov[1].x, ov[2].x, bitmask), xor_or(ov[3].x, ov[4].x, bitmask), xor_or(ov[5].x, ov[6].x, bitmask)),
                            xor_or(ov[7].x, ov[8].x, bitmask));
                        if (__all_sync(0xffffffffu, (bad & 1u) == 0) && (h == 15 || n > 0)) break;
                        if (h != 15) __nanosleep(400);
                        if (++n > SPIN_LIMIT) __trap();
#pragma unroll
                        for (int j = 0; j < 5; j++) ldu64_stale(ml[j], j < 4 ? pml + j * 128 : pml4, bit);
#pragma unroll
                        for (int it = 0; it < 9; it++) ld128_stale(ov[it], it < 8 ? pr + it * PRS : pr8, bit);
                    }
                    float mj[5];
#pragma unroll
                    for (int j = 0; j < 5; j++) mj[j] = __uint_as_float((uint32_t)ml[j]);
                    const float M = warp_max(fmaxf(fmaxf(fmaxf(mj[0], mj[1]), fmaxf(mj[2], mj[3])), mj[4]));
                    float wc[5], Ls = 0.f;
#pragma unroll
                    for (int j = 0; j < 5; j++) {
                        wc[j] = ex2(mj[j] - M);
                        if (j == 4 && lane >= G - 128) wc[j] = 0.f;
                        Ls += wc[j] * __uint_as_float((uint32_t)(ml[j] >> 32));
                    }
                    float a0 = 0.f, a1 = 0.f, a2 = 0.f, a3 = 0.f;
#pragma unroll
                    for (int it = 0; it < 9; it++) {
                        const float wv = __shfl_sync(0xffffffffu, wc[it >> 1], 16 * (it & 1) + (lane >> 1));
                        a0 += wv * __uint_as_float(ov[it].x);
                        a1 += wv * __uint_as_float(ov[it].y);
                        a2 += wv * __uint_as_float(ov[it].z);
                        a3 += wv * __uint_as_float(ov[it].w);
                        if (it == 0) Ls += __shfl_xor_sync(0xffffffffu, Ls, 1);
                    }
                    const bool up = lane & 2;
                    float ax = (up ? a2 : a0) + __shfl_xor_sync(0xffffffffu, up ? a0 : a2, 2);
                    float ay = (up ? a3 : a1) + __shfl_xor_sync(0xffffffffu, up ? a1 : a3, 2);
                    Ls += __shfl_xor_sync(0xffffffffu, Ls, 2);
#pragma unroll
                    for (int o = 4; o <= 16; o <<= 1) {
                        ax += __shfl_xor_sync(0xffffffffu, ax, o);
                        ay += __shfl_xor_sync(0xffffffffu, ay, o);
                        Ls += __shfl_xor_sync(0xffffffffu, Ls, o);
                    }
                    float inv;
                    asm("rcp.approx.ftz.f32 %0, %1;" : "=f"(inv) : "f"(Ls));
                    const uint32_t o2 = pack_bf16(ax * inv, ay * inv);
                    if (isY) {
                        if (lane < 4) s_ofin[h * 4 + lane] = o2;
                        __syncwarp();
                        if (h == 7 && lane == 0) mbar_arrive(bar_ofin);
                    } else {
                        project(y, wf, o2, lane);
                    }
                }
                if (h >= 14) {
                    const uint32_t obit = (h == 15) ? bit : bit ^ 1u;
                    char* dst = reinterpret_cast<char*>(g_ol + ((size_t)(56 + g) * 64 + slice) * 2) + t4 * 8;
#pragma unroll
                    for (int j = 0; j < 7; j++) st64(dst + (size_t)j * 8 * 64 * 32, pt_enc(y[j][0], obit), __float_as_uint(y[j][2]));
                }
            }
            if (cta == 127 && lane == 0) {
                asm volatile("st.relaxed.gpu.global.u32 [%0], %1;" ::"l"(&g_epoch), "r"(tag) : "memory");
            }
        }
    } else {
        uint32_t tag;
        asm volatile("ld.relaxed.gpu.global.u32 %0, [%1];" : "=r"(tag) : "l"(&g_epoch) : "memory");
        const int g = lane >> 2, t4 = lane & 3;
        if (has_task) {
            const int tb = cta >> 6, qs = cta & 63;
            const int r = threadIdx.x >> 3, c8 = threadIdx.x & 7;
            const uint2* xp = reinterpret_cast<const uint2*>(p.x[tb] + 28 * r);
            uint2 xv[7];
#pragma unroll
            for (int i = 0; i < 7; i++)
                asm volatile("ld.global.nc.v2.u32 {%0,%1}, [%2];" : "=r"(xv[i].x), "=r"(xv[i].y) : "l"(xp + i));
            asm volatile("bar.sync 2, %0;" ::"n"(NTHREADS) : "memory");
            mbar_wait(bar_wq, 0);
            const uint4* wv = reinterpret_cast<const uint4*>(smem + L::RING + (NS - 4) * STAGE_BYTES) + 28 * r * 8 + c8;
            float acc[8];
#pragma unroll
            for (int j = 0; j < 8; j++) acc[j] = 0.f;
#pragma unroll
            for (int i = 0; i < 28; i++) {
                const uint32_t xw = (i & 2) ? xv[i >> 2].y : xv[i >> 2].x;
                const float xs = (i & 1) ? bf_hi(xw) : bf_lo(xw);
                const uint4 v = wv[i * 8];
                acc[0] += xs * bf_lo(v.x); acc[1] += xs * bf_hi(v.x);
                acc[2] += xs * bf_lo(v.y); acc[3] += xs * bf_hi(v.y);
                acc[4] += xs * bf_lo(v.z); acc[5] += xs * bf_hi(v.z);
                acc[6] += xs * bf_lo(v.w); acc[7] += xs * bf_hi(v.w);
            }
#pragma unroll
            for (int j = 0; j < 8; j++) {
                acc[j] += __shfl_xor_sync(0xffffffffu, acc[j], 8);
                acc[j] += __shfl_xor_sync(0xffffffffu, acc[j], 16);
            }
            if (lane < 8) {
                float4* d = reinterpret_cast<float4*>(s_red + warp * 64 + lane * 8);
                d[0] = make_float4(acc[0], acc[1], acc[2], acc[3]);
                d[1] = make_float4(acc[4], acc[5], acc[6], acc[7]);
            }
            asm volatile("bar.sync 1, %0;" ::"n"(W * 32) : "memory");
            if (threadIdx.x < 16) {
                const int il = threadIdx.x >> 2;
                float q[4];
#pragma unroll
                for (int k = 0; k < 4; k++) {
                    const int d = 16 * il + 2 * t4 + (k & 1) + 8 * (k >> 1);
                    q[k] = 0.f;
#pragma unroll
                    for (int w = 0; w < W; w++) q[k] += s_red[w * 64 + d];
                }
                ll_store(g_q + ((tb * 16 + (qs >> 2)) * 16 + (qs & 3) * 4 + il) * 4 + t4,
                         pack_bf16(q[0], q[1]), pack_bf16(q[2], q[3]), tag + 1);
            }
            __syncwarp();
            if (lane == 0) mbar_arrive(bar_wqdone);
        } else {
            asm volatile("bar.sync 2, %0;" ::"n"(NTHREADS) : "memory");
        }
        tag += 1;
        const uint32_t bit = tag & 1u;

        float acc[4][4];
#pragma unroll
        for (int i = 0; i < 4; i++) { acc[i][0] = 0.f; acc[i][1] = 0.f; acc[i][2] = 0.f; acc[i][3] = 0.f; }
        float m0 = -INFINITY, m1 = -INFINITY;
        float lacc[4] = {0.f, 0.f, 0.f, 0.f};
        const uint32_t ones[4] = {0x3f803f80u, 0x3f803f80u, 0x3f803f80u, 0x3f803f80u};
        uint32_t qf[16][2];
        int cur = 0;
        const uint32_t krow = (lane & 7) + 8 * ((lane >> 3) & 1), vrow = (lane & 7) + 8 * (lane >> 4);
        const uint32_t koff = krow * 128 + (((lane >> 4) ^ (krow & 7)) << 4);
        const uint32_t voff = TILE_BYTES + vrow * 128 + ((((lane >> 3) & 1) ^ (vrow & 7)) << 4);
        const float SC = 0.0625f * 1.4426950408889634f;
        char* const ydst = reinterpret_cast<char*>(g_ol + ((size_t)(8 * warp + g) * 64 + slice) * 2) + t4 * 8;
        int s = warp;
        uint32_t ph = 0;
        mbar_wait(bar_q, 0);
#pragma unroll
        for (int i = 0; i < 16; i++) {
            const uint2 v = s_q0[((g & 1) * 16 + i) * 4 + t4];
            qf[i][0] = v.x;
            qf[i][1] = v.y;
        }
        while (true) {
            mbar_wait(bar_full + s * 8, ph);
            const int t = s_tk[s];
            const int h = t >> 12;
            if (h != cur) {
                while (cur < h) {
                    float* sl = s_slots + warp * 2 * SLOT_STRIDE + 16 * t4 + 8 * (t4 >> 1) + g;
                    if (lane == 0) *reinterpret_cast<float4*>(s_slotml + warp * 4) = make_float4(m0, lacc[0], m1, lacc[1]);
#pragma unroll
                    for (int j = 0; j < 4; j++) {
                        sl[80 * j] = acc[j][0];
                        sl[80 * j + SLOT_STRIDE] = acc[j][1];
                        sl[80 * j + 8] = acc[j][2];
                        sl[80 * j + 8 + SLOT_STRIDE] = acc[j][3];
                    }
                    uint4* po = g_po + ((size_t)(cur * 32 + 8 * warp + (lane >> 2)) * G + cta) * 4 + (lane & 3);
                    ulonglong2* pml = g_pml + ((cur * G + cta) * 2 + (warp >> 1)) * 2 + lane;
                    asm volatile("bar.sync 1, %0;" ::"n"(W * 32) : "memory");
                    float2 mlw[W];
                    float4 sv[W];
                    float M = -INFINITY;
#pragma unroll
                    for (int w = 0; w < W; w++) {
                        mlw[w] = *reinterpret_cast<const float2*>(s_slotml + w * 4 + (warp & 2));
                        sv[w] = *reinterpret_cast<const float4*>(s_slots + (w * 2 + (warp >> 1)) * SLOT_STRIDE + 160 * (warp & 1) + 4 * lane + (lane & 24));
                        M = fmaxf(M, mlw[w].x);
                    }
                    const float R = (M == -INFINITY) ? 0.f : M;
                    float4 o = make_float4(0.f, 0.f, 0.f, 0.f);
                    float Lw = 0.f;
#pragma unroll
                    for (int w = 0; w < W; w++) {
                        const float f = ex2(mlw[w].x - R);
                        Lw += f * mlw[w].y;
                        o.x += f * sv[w].x; o.y += f * sv[w].y; o.z += f * sv[w].z; o.w += f * sv[w].w;
                    }
                    st128(po, pt_enc(o.x, bit), __float_as_uint(o.y), __float_as_uint(o.z), __float_as_uint(o.w));
                    const bool mlwriter = !(warp & 1) && lane < 2;
                    if (mlwriter) ll_store(pml, __float_as_uint(M), __float_as_uint(M), pt_enc(Lw, bit));
                    if (cur == 13) {
                        st128(po + 2 * 32 * G * 4, bit ^ 1u, 0u, 0u, 0u);
                        if (mlwriter) ll_store(pml + 2 * G * 4, 0u, 0u, bit ^ 1u);
                        if (isY) {
                            st64(ydst, bit ^ 1u, 0u);
                            if (warp < 3) st64(ydst + 4 * 8 * 64 * 32, bit ^ 1u, 0u);
                        }
                    }
#pragma unroll
                    for (int i = 0; i < 4; i++) { acc[i][0] = 0.f; acc[i][1] = 0.f; acc[i][2] = 0.f; acc[i][3] = 0.f; }
                    m0 = -INFINITY; m1 = -INFINITY;
                    lacc[0] = 0.f; lacc[1] = 0.f; lacc[2] = 0.f; lacc[3] = 0.f;
                    cur++;
                    asm volatile("bar.sync 1, %0;" ::"n"(W * 32) : "memory");
                }
                if (h >= 16) break;
                mbar_wait(h > 3 ? bar_q3 : bar_q2, 0);
#pragma unroll
                for (int i = 0; i < 16; i++) {
                    const uint2 v = s_q0[h * 128 + ((g & 1) * 16 + i) * 4 + t4];
                    qf[i][0] = v.x;
                    qf[i][1] = v.y;
                }
            }
            const uint32_t stage = sbase + L::RING + s * STAGE_BYTES;
            float sc[4][4];
#pragma unroll
            for (int c = 0; c < 4; c++) { sc[c][0] = 0.f; sc[c][1] = 0.f; sc[c][2] = 0.f; sc[c][3] = 0.f; }
            const uint32_t kb = stage + koff;
#pragma unroll
            for (int i = 0; i < 16; i++) {
                uint32_t a[4];
                ldsm4(a, (kb ^ ((i & 3) << 5)) + (i >> 2) * 2048);
                mma16816(sc[i & 3], a, qf[i][0], qf[i][1]);
            }
            const float s0 = ((sc[0][0] + sc[1][0]) + (sc[2][0] + sc[3][0])) * SC;
            const float s1 = ((sc[0][1] + sc[1][1]) + (sc[2][1] + sc[3][1])) * SC;
            const float s2 = ((sc[0][2] + sc[1][2]) + (sc[2][2] + sc[3][2])) * SC;
            const float s3 = ((sc[0][3] + sc[1][3]) + (sc[2][3] + sc[3][3])) * SC;
            float n0 = fmaxf(s0, s2), n1 = fmaxf(s1, s3);
            if (__any_sync(0xffffffffu, (n0 > m0) | (n1 > m1))) {
                n0 = fmaxf(warp_max(n0), m0);
                n1 = fmaxf(warp_max(n1), m1);
                const float f0 = ex2(m0 - n0), f1 = ex2(m1 - n1);
                m0 = n0; m1 = n1;
                lacc[0] *= f0; lacc[1] *= f1; lacc[2] *= f0; lacc[3] *= f1;
#pragma unroll
                for (int i = 0; i < 4; i++) { acc[i][0] *= f0; acc[i][1] *= f1; acc[i][2] *= f0; acc[i][3] *= f1; }
            }
            const float p0 = ex2(s0 - m0), p1 = ex2(s1 - m1), p2 = ex2(s2 - m0), p3 = ex2(s3 - m1);
            const uint32_t b0 = movtrans(pack_bf16(p0, p1));
            const uint32_t b1 = movtrans(pack_bf16(p2, p3));
            mma16816(lacc, ones, b0, b1);
            mbar_wait(bar_fullv + s * 8, ph);
            const uint32_t vb = stage + voff;
#pragma unroll
            for (int q = 0; q < 4; q++) {
                const uint32_t c0 = ((g >> 1) == q) ? b0 : 0u, c1 = ((g >> 1) == q) ? b1 : 0u;
#pragma unroll
                for (int j = 0; j < 4; j++) {
                    uint32_t a[4];
                    ldsm4t(a, (vb ^ (q << 5)) + j * 2048);
                    mma16816(acc[j], a, c0, c1);
                }
            }
            __syncwarp();
            if (lane == 0) mbar_arrive(bar_empty + s * 8);
            s += W;
            if (s >= NS) { s -= NS; ph ^= 1; }
        }

        if (isY) {
            mbar_wait(bar_ofin, 0);
            float y[7][4];
#pragma unroll
            for (int j = 0; j < 7; j++) { y[j][0] = 0.f; y[j][1] = 0.f; y[j][2] = 0.f; y[j][3] = 0.f; }
            float2* red = reinterpret_cast<float2*>(s_red);
#pragma unroll 1
            for (int k = warp; k < 8; k += W) {
                const uint32_t o2 = s_ofin[k * 4 + t4];
                int ws = s_tk[31] + (k >> 1);
                if (ws >= NS) ws -= NS;
                mbar_wait(bar_wo + k * 8, 0);
                uint32_t wf[14][4];
                load_wo_frags(wf, sbase + L::RING + ws * STAGE_BYTES + (k & 1) * SEG_BYTES, lane);
                project(y, wf, o2, lane);
            }
#pragma unroll
            for (int j = 0; j < 7; j++) red[(warp * 7 + j) * 32 + lane] = make_float2(y[j][0], y[j][2]);
            asm volatile("bar.sync 1, %0;" ::"n"(W * 32) : "memory");
#pragma unroll
            for (int jj = 0; jj < 2; jj++) {
                const int j = warp + 4 * jj;
                if (j < 7) {
                    float vx = 0.f, vy = 0.f;
#pragma unroll
                    for (int w = 0; w < W; w++) {
                        const float2 v = red[(w * 7 + j) * 32 + lane];
                        vx += v.x;
                        vy += v.y;
                    }
                    st64(ydst + jj * 4 * 8 * 64 * 32, pt_enc(vx, bit), __float_as_uint(vy));
                }
            }
        }
        if (isX && slice < 56 && !(warp & 1)) {
            const bool fb = warp < 2;
            const uint32_t bitmask = 0u - bit;
            const uint4* src = g_ol + (size_t)((fb ? 56 : 0) + slice) * 64 * 2 + lane;
            const int et = 2 * (lane & 1) + ((lane >> 1) & 1), es = (lane >> 2) & 1;
            const int col = (fb ? DM : 0) + 64 * (slice >> 3) + 16 * et + 8 * es + (slice & 7);
            __nv_bfloat16* dst = p.out + col;
            unsigned n = 0;
            while (true) {
                uint4 v[4];
#pragma unroll
                for (int i = 0; i < 4; i++) ld2x64(v[i], src + i * 32);
                const uint32_t bad = or3(xor_or(v[0].x, v[0].z, bitmask), xor_or(v[1].x, v[1].z, bitmask),
                                         xor_or(v[2].x, v[2].z, bitmask)) | xor_or(v[3].x, v[3].z, bitmask);
                const bool done = __all_sync(0xffffffffu, (bad & 1u) == 0);
                const float a0 = (__uint_as_float(v[0].x) + __uint_as_float(v[1].x)) + (__uint_as_float(v[2].x) + __uint_as_float(v[3].x));
                const float a1 = (__uint_as_float(v[0].y) + __uint_as_float(v[1].y)) + (__uint_as_float(v[2].y) + __uint_as_float(v[3].y));
                const float a2 = (__uint_as_float(v[0].z) + __uint_as_float(v[1].z)) + (__uint_as_float(v[2].z) + __uint_as_float(v[3].z));
                const float a3 = (__uint_as_float(v[0].w) + __uint_as_float(v[1].w)) + (__uint_as_float(v[2].w) + __uint_as_float(v[3].w));
                if (done || n == 0) {
                    const bool u1 = lane & 2, u2 = lane & 4;
                    const float bx = (u1 ? a2 : a0) + __shfl_xor_sync(0xffffffffu, u1 ? a0 : a2, 2);
                    const float by = (u1 ? a3 : a1) + __shfl_xor_sync(0xffffffffu, u1 ? a1 : a3, 2);
                    float c = (u2 ? by : bx) + __shfl_xor_sync(0xffffffffu, u2 ? bx : by, 4);
                    c += __shfl_xor_sync(0xffffffffu, c, 8);
                    c += __shfl_xor_sync(0xffffffffu, c, 16);
                    if (done && lane < 8) *dst = __float2bfloat16(c);
                    if (done) break;
                }
                if (++n > SPIN_LIMIT) __trap();
            }
        }
    }
}

constexpr int FB_SPLIT = 64;
__device__ float g_fq[2 * 4096];
__device__ float g_fp[16 * FB_SPLIT * 8 * 2 * 264];

__global__ void fb_q_kernel(const __nv_bfloat16* x, const __nv_bfloat16* wq, int b) {
    const int n = blockIdx.x * blockDim.x + threadIdx.x;
    float a = 0.f;
    for (int k = 0; k < DM; k++) a += __bfloat162float(x[k]) * __bfloat162float(wq[(size_t)k * 4096 + n]);
    g_fq[b * 4096 + n] = __bfloat162float(__float2bfloat16(a));
}
__global__ void fb_attn_kernel(const uint4* k, const uint4* v, int b) {
    const int hk = blockIdx.y, warp = threadIdx.x >> 5, lane = threadIdx.x & 31;
    float q[2][8], o[2][8], m[2] = {-INFINITY, -INFINITY}, l[2] = {0.f, 0.f};
    for (int h = 0; h < 2; h++)
        for (int j = 0; j < 8; j++) { q[h][j] = g_fq[b * 4096 + (hk * 2 + h) * 256 + lane * 8 + j]; o[h][j] = 0.f; }
    const int n = 65536 / FB_SPLIT / 8;
    const size_t row0 = (size_t)hk * 65536 + (size_t)(blockIdx.x * 8 + warp) * n;
    for (int i = 0; i < n; i++) {
        const uint4 kk = k[(row0 + i) * 32 + lane], vv = v[(row0 + i) * 32 + lane];
        const float kf[8] = {bf_lo(kk.x), bf_hi(kk.x), bf_lo(kk.y), bf_hi(kk.y), bf_lo(kk.z), bf_hi(kk.z), bf_lo(kk.w), bf_hi(kk.w)};
        const float vf[8] = {bf_lo(vv.x), bf_hi(vv.x), bf_lo(vv.y), bf_hi(vv.y), bf_lo(vv.z), bf_hi(vv.z), bf_lo(vv.w), bf_hi(vv.w)};
#pragma unroll
        for (int h = 0; h < 2; h++) {
            float s = 0.f;
#pragma unroll
            for (int j = 0; j < 8; j++) s += q[h][j] * kf[j];
            for (int d = 16; d >= 1; d >>= 1) s += __shfl_xor_sync(0xffffffffu, s, d);
            s *= 0.0625f * 1.4426950408889634f;
            const float mn = fmaxf(m[h], s), f = ex2(m[h] - mn), pr = ex2(s - mn);
            m[h] = mn;
            l[h] = l[h] * f + pr;
#pragma unroll
            for (int j = 0; j < 8; j++) o[h][j] = o[h][j] * f + pr * vf[j];
        }
    }
    for (int h = 0; h < 2; h++) {
        float* d = g_fp + ((((size_t)(b * 8 + hk) * FB_SPLIT + blockIdx.x) * 8 + warp) * 2 + h) * 264;
        for (int j = 0; j < 8; j++) d[lane * 8 + j] = o[h][j];
        if (lane == 0) { d[256] = m[h]; d[257] = l[h]; }
    }
}
__global__ void fb_merge_kernel() {
    const int hq = blockIdx.x;
    const float* base = g_fp + ((size_t)(hq >> 1) * FB_SPLIT * 8 * 2 + (hq & 1)) * 264;
    float M = -INFINITY, Ls = 0.f, a = 0.f;
    for (int i = 0; i < FB_SPLIT * 8; i++) M = fmaxf(M, base[(size_t)i * 528 + 256]);
    for (int i = 0; i < FB_SPLIT * 8; i++) {
        const float w = ex2(base[(size_t)i * 528 + 256] - M);
        Ls += w * base[(size_t)i * 528 + 257];
        a += w * base[(size_t)i * 528 + threadIdx.x];
    }
    g_fq[hq * 256 + threadIdx.x] = __bfloat162float(__float2bfloat16(a / Ls));
}
__global__ void fb_out_kernel(const __nv_bfloat16* wo, __nv_bfloat16* out, int b) {
    const int n = blockIdx.x * 64 + threadIdx.x;
    float a = 0.f;
    for (int k = 0; k < 4096; k++) a += g_fq[b * 4096 + k] * __bfloat162float(wo[(size_t)k * DM + n]);
    out[b * DM + n] = __float2bfloat16(a);
}

typedef CUresult (*EncodeFn)(CUtensorMap*, CUtensorMapDataType, cuuint32_t, void*, const cuuint64_t*, const cuuint64_t*,
                             const cuuint32_t*, const cuuint32_t*, CUtensorMapInterleave, CUtensorMapSwizzle,
                             CUtensorMapL2promotion, CUtensorMapFloatOOBfill);

void encode_kv(EncodeFn enc, CUtensorMap* m, const void* ptr) {
    cuuint64_t gd[3] = {64, 8ull * 65536ull, 4};
    cuuint64_t gs[2] = {512, 128};
    cuuint32_t box[3] = {64, 16, 4};
    cuuint32_t es[3] = {1, 1, 1};
    enc(m, CU_TENSOR_MAP_DATA_TYPE_BFLOAT16, 3, const_cast<void*>(ptr), gd, gs, box, es, CU_TENSOR_MAP_INTERLEAVE_NONE,
        CU_TENSOR_MAP_SWIZZLE_128B, CU_TENSOR_MAP_L2_PROMOTION_L2_256B, CU_TENSOR_MAP_FLOAT_OOB_FILL_NONE);
}

void encode_wo(EncodeFn enc, CUtensorMap* m, const void* ptr) {
    cuuint64_t gd[3] = {64, 4096, 7};
    cuuint64_t gs[2] = {DM * 2, 128};
    cuuint32_t box[3] = {64, 8, 7};
    cuuint32_t es[3] = {1, 1, 1};
    enc(m, CU_TENSOR_MAP_DATA_TYPE_BFLOAT16, 3, const_cast<void*>(ptr), gd, gs, box, es, CU_TENSOR_MAP_INTERLEAVE_NONE,
        CU_TENSOR_MAP_SWIZZLE_128B, CU_TENSOR_MAP_L2_PROMOTION_L2_128B, CU_TENSOR_MAP_FLOAT_OOB_FILL_NONE);
}

void encode_wq(EncodeFn enc, CUtensorMap* m, const void* ptr) {
    cuuint64_t gd[2] = {4096, 448};
    cuuint64_t gs[1] = {8192};
    cuuint32_t box[2] = {64, 224};
    cuuint32_t es[2] = {1, 1};
    enc(m, CU_TENSOR_MAP_DATA_TYPE_BFLOAT16, 2, const_cast<void*>(ptr), gd, gs, box, es, CU_TENSOR_MAP_INTERLEAVE_NONE,
        CU_TENSOR_MAP_SWIZZLE_NONE, CU_TENSOR_MAP_L2_PROMOTION_L2_128B, CU_TENSOR_MAP_FLOAT_OOB_FILL_NONE);
}

}

extern "C" void kernel_launch(void* const* d_in, const int* in_sizes, int n_in, void* d_out, int out_size) {
    (void)in_sizes; (void)n_in; (void)out_size;
    static EncodeFn enc = nullptr;
    static int mode = -1;
    if (mode < 0) {
        cudaDriverEntryPointQueryResult qr;
        void* fn = nullptr;
        cudaGetDriverEntryPoint("cuTensorMapEncodeTiled", &fn, cudaEnableDefault, &qr);
        enc = (EncodeFn)fn;
        int dev = 0, sms = 0, occ = 0;
        cudaGetDevice(&dev);
        cudaDeviceGetAttribute(&sms, cudaDevAttrMultiProcessorCount, dev);
        const bool attr_ok =
            cudaFuncSetAttribute(fused_decode_kernel, cudaFuncAttributeMaxDynamicSharedMemorySize, L::SIZE) == cudaSuccess;
        if (attr_ok) cudaOccupancyMaxActiveBlocksPerMultiprocessor(&occ, fused_decode_kernel, NTHREADS, L::SIZE);
        mode = (enc != nullptr && attr_ok && sms * occ >= G) ? 1 : 0;
        (void)cudaGetLastError();
    }
    if (mode == 1) {
        Params p;
        for (int b = 0; b < 2; b++) {
            p.x[b] = (const __nv_bfloat16*)d_in[5 * b + 0];
            encode_kv(enc, &p.km[b], d_in[5 * b + 1]);
            encode_kv(enc, &p.vm[b], d_in[5 * b + 2]);
            encode_wq(enc, &p.wqm[b], d_in[5 * b + 3]);
            encode_wo(enc, &p.wom[b], d_in[5 * b + 4]);
        }
        p.out = (__nv_bfloat16*)d_out;
        fused_decode_kernel<<<G, NTHREADS, L::SIZE>>>(p);
    } else {
        for (int b = 0; b < 2; b++) {
            fb_q_kernel<<<16, 256>>>((const __nv_bfloat16*)d_in[5 * b], (const __nv_bfloat16*)d_in[5 * b + 3], b);
            fb_attn_kernel<<<dim3(FB_SPLIT, 8), 256>>>((const uint4*)d_in[5 * b + 1], (const uint4*)d_in[5 * b + 2], b);
        }
        fb_merge_kernel<<<32, 256>>>();
        for (int b = 0; b < 2; b++)
            fb_out_kernel<<<7, 64>>>((const __nv_bfloat16*)d_in[5 * b + 4], (__nv_bfloat16*)d_out, b);
    }
}
```

```cpp
#include <cuda_runtime.h>
#include <cuda_bf16.h>
#include <cuda.h>
#include <stdint.h>

namespace {

constexpr int G = 132;
constexpr int W = 4;
constexpr int NTHREADS = (W + 2) * 32;
constexpr int TILE_BYTES = 8192;
constexpr int STAGE_BYTES = 2 * TILE_BYTES;
constexpr int TOTAL = 65536;
constexpr int DM = 448;
constexpr int SEG_BYTES = 8 * DM * 2;
constexpr int SLOT_STRIDE = 320;
constexpr int PROG_END = 1 << 30;
constexpr int NS = 12;
constexpr int K0 = 4;
constexpr int Q_DELAY = 1500;
constexpr int MERGE_DELAY = 2500;
constexpr int CAP = 4, CAP_END = 3;
constexpr int END_ZONE = 1000;
constexpr unsigned SPIN_LIMIT = 1u << 22;

struct Params {
    const __nv_bfloat16* x[2];
    __nv_bfloat16* out;
    CUtensorMap km[2];
    CUtensorMap vm[2];
    CUtensorMap wqm[2];
    CUtensorMap wom[2];
};

typedef unsigned long long u64;

__device__ unsigned int g_epoch;
__device__ unsigned int g_ticket;
__device__ ulonglong2 g_q[16 * 2 * 16 * 4];
__device__ uint4 g_po[16 * 32 * G * 4];
__device__ ulonglong2 g_pml[16 * G * 2 * 2];
__device__ uint4 g_ol[2 * 56 * 64 * 2];

__device__ __forceinline__ uint32_t smem_u32(const void* p) { return (uint32_t)__cvta_generic_to_shared(p); }
__device__ __forceinline__ void mbar_init(uint32_t bar, uint32_t cnt) {
    asm volatile("mbarrier.init.shared::cta.b64 [%0], %1;" ::"r"(bar), "r"(cnt) : "memory");
}
__device__ __forceinline__ void mbar_expect_tx(uint32_t bar, uint32_t bytes) {
    asm volatile("mbarrier.arrive.expect_tx.shared::cta.b64 _, [%0], %1;" ::"r"(bar), "r"(bytes) : "memory");
}
__device__ __forceinline__ void mbar_arrive(uint32_t bar) {
    asm volatile("mbarrier.arrive.shared::cta.b64 _, [%0];" ::"r"(bar) : "memory");
}
__device__ __forceinline__ bool mbar_try(uint32_t bar, uint32_t parity) {
    uint32_t ok;
    asm volatile("{\n.reg .pred p;\nmbarrier.try_wait.parity.shared::cta.b64 p, [%1], %2;\nselp.u32 %0, 1, 0, p;\n}"
                 : "=r"(ok) : "r"(bar), "r"(parity) : "memory");
    return ok != 0;
}
__device__ __forceinline__ void mbar_wait(uint32_t bar, uint32_t parity) {
    unsigned n = 0;
    while (!mbar_try(bar, parity)) {
        if (++n > SPIN_LIMIT) __trap();
    }
}
__device__ __forceinline__ void tma3d(uint32_t dst, const CUtensorMap* m, int row, uint32_t bar, uint64_t pol) {
    asm volatile(
        "cp.async.bulk.tensor.3d.shared::cluster.global.mbarrier::complete_tx::bytes.L2::cache_hint "
        "[%0], [%1, {%3, %4, %3}], [%2], %5;" ::"r"(dst), "l"(m), "r"(bar), "r"(0), "r"(row), "l"(pol)
        : "memory");
}
__device__ __forceinline__ uint64_t evict_first_policy() {
    uint64_t pol;
    asm volatile("createpolicy.fractional.L2::evict_first.b64 %0, 1.0;" : "=l"(pol));
    return pol;
}
__device__ __forceinline__ void ldsm4(uint32_t (&r)[4], uint32_t addr) {
    asm volatile("ldmatrix.sync.aligned.m8n8.x4.shared.b16 {%0,%1,%2,%3}, [%4];"
                 : "=r"(r[0]), "=r"(r[1]), "=r"(r[2]), "=r"(r[3]) : "r"(addr) : "memory");
}
__device__ __forceinline__ void ldsm4t(uint32_t (&r)[4], uint32_t addr) {
    asm volatile("ldmatrix.sync.aligned.m8n8.x4.trans.shared.b16 {%0,%1,%2,%3}, [%4];"
                 : "=r"(r[0]), "=r"(r[1]), "=r"(r[2]), "=r"(r[3]) : "r"(addr) : "memory");
}
__device__ __forceinline__ void mma16816(float (&c)[4], const uint32_t (&a)[4], uint32_t b0, uint32_t b1) {
    asm volatile("mma.sync.aligned.m16n8k16.row.col.f32.bf16.bf16.f32 {%0,%1,%2,%3}, {%4,%5,%6,%7}, {%8,%9}, {%0,%1,%2,%3};"
                 : "+f"(c[0]), "+f"(c[1]), "+f"(c[2]), "+f"(c[3])
                 : "r"(a[0]), "r"(a[1]), "r"(a[2]), "r"(a[3]), "r"(b0), "r"(b1));
}
__device__ __forceinline__ uint32_t movtrans(uint32_t a) {
    uint32_t d;
    asm volatile("movmatrix.sync.aligned.m8n8.trans.b16 %0, %1;" : "=r"(d) : "r"(a));
    return d;
}
__device__ __forceinline__ float ex2(float x) {
    float y;
    asm("ex2.approx.ftz.f32 %0, %1;" : "=f"(y) : "f"(x));
    return y;
}
__device__ __forceinline__ uint32_t pack_bf16(float lo, float hi) {
    uint32_t d;
    asm("cvt.rn.bf16x2.f32 %0, %1, %2;" : "=r"(d) : "f"(hi), "f"(lo));
    return d;
}
__device__ __forceinline__ float bf_lo(uint32_t v) { return __uint_as_float(v << 16); }
__device__ __forceinline__ float bf_hi(uint32_t v) { return __uint_as_float(v & 0xffff0000u); }
__device__ __forceinline__ float warp_max(float v) {
    int k = __float_as_int(v);
    k ^= (k >> 31) & 0x7fffffff;
    k = __reduce_max_sync(0xffffffffu, k);
    k ^= (k >> 31) & 0x7fffffff;
    return __int_as_float(k);
}

__device__ __forceinline__ uint32_t ticket_base(uint32_t epoch) { return (~epoch & 0x7ffu) << 20; }

__device__ __forceinline__ u64 ll_word(uint32_t v, uint32_t tag) { return ((u64)tag << 32) | v; }
__device__ __forceinline__ void ll_store(ulonglong2* p, uint32_t a, uint32_t b, uint32_t tag) {
    asm volatile("st.relaxed.gpu.global.v2.b64 [%0], {%1, %2};" ::"l"(p), "l"(ll_word(a, tag)), "l"(ll_word(b, tag)) : "memory");
}
__device__ __forceinline__ bool ll_ok(u64 x, u64 y, uint32_t tag) {
    return ((uint32_t)(x >> 32) == tag) & ((uint32_t)(y >> 32) == tag);
}
__device__ __forceinline__ uint32_t pt_enc(float v, uint32_t bit) { return (__float_as_uint(v) & ~1u) | bit; }
__device__ __forceinline__ uint32_t xor_or(uint32_t a, uint32_t b, uint32_t m) {
    uint32_t d;
    asm("lop3.b32 %0, %1, %2, %3, 0x7e;" : "=r"(d) : "r"(a), "r"(b), "r"(m));
    return d;
}
__device__ __forceinline__ uint32_t or3(uint32_t a, uint32_t b, uint32_t c) {
    uint32_t d;
    asm("lop3.b32 %0, %1, %2, %3, 0xfe;" : "=r"(d) : "r"(a), "r"(b), "r"(c));
    return d;
}
__device__ __forceinline__ void st128(uint4* p, uint32_t a, uint32_t b, uint32_t c, uint32_t d) {
    asm volatile("{\n.reg .b128 t;\n.reg .b64 lo, hi;\nmov.b64 lo, {%1, %2};\nmov.b64 hi, {%3, %4};\nmov.b128 t, {lo, hi};\n"
                 "st.relaxed.gpu.global.b128 [%0], t;\n}" ::"l"(p), "r"(a), "r"(b), "r"(c), "r"(d) : "memory");
}
__device__ __forceinline__ void ld128(uint4& v, const uint4* p) {
    asm volatile("{\n.reg .b128 t;\n.reg .b64 lo, hi;\nld.relaxed.gpu.global.b128 t, [%4];\nmov.b128 {lo, hi}, t;\n"
                 "mov.b64 {%0, %1}, lo;\nmov.b64 {%2, %3}, hi;\n}"
                 : "=r"(v.x), "=r"(v.y), "=r"(v.z), "=r"(v.w) : "l"(p) : "memory");
}
__device__ __forceinline__ void ld128_stale(uint4& v, const uint4* p, uint32_t bit) {
    asm volatile("{\n.reg .pred p;\n.reg .b32 u;\n.reg .b128 t;\n.reg .b64 lo, hi;\nand.b32 u, %0, 1;\nsetp.ne.u32 p, u, %5;\n"
                 "mov.b64 lo, {%0, %1};\nmov.b64 hi, {%2, %3};\nmov.b128 t, {lo, hi};\n"
                 "@p ld.relaxed.gpu.global.b128 t, [%4];\nmov.b128 {lo, hi}, t;\nmov.b64 {%0, %1}, lo;\nmov.b64 {%2, %3}, hi;\n}"
                 : "+r"(v.x), "+r"(v.y), "+r"(v.z), "+r"(v.w) : "l"(p), "r"(bit) : "memory");
}
__device__ __forceinline__ void st64(void* p, uint32_t a, uint32_t b) {
    asm volatile("{\n.reg .b64 t;\nmov.b64 t, {%1, %2};\nst.relaxed.gpu.global.b64 [%0], t;\n}" ::"l"(p), "r"(a), "r"(b) : "memory");
}
__device__ __forceinline__ void ld2x64(uint4& v, const uint4* p) {
    asm volatile("{\n.reg .b64 lo, hi;\nld.relaxed.gpu.global.v2.b64 {lo, hi}, [%4];\nmov.b64 {%0, %1}, lo;\nmov.b64 {%2, %3}, hi;\n}"
                 : "=r"(v.x), "=r"(v.y), "=r"(v.z), "=r"(v.w) : "l"(p) : "memory");
}
__device__ __forceinline__ void ldu64(u64& v, const void* p) {
    asm volatile("ld.relaxed.gpu.global.b64 %0, [%1];" : "=l"(v) : "l"(p) : "memory");
}
__device__ __forceinline__ void ldu64_stale(u64& v, const void* p, uint32_t bit) {
    asm volatile("{\n.reg .pred p;\n.reg .b32 a, b;\nmov.b64 {a, b}, %0;\nand.b32 b, b, 1;\nsetp.ne.u32 p, b, %2;\n"
                 "@p ld.relaxed.gpu.global.b64 %0, [%1];\n}" : "+l"(v) : "l"(p), "r"(bit) : "memory");
}
__device__ __forceinline__ void mma1688(float (&c)[4], uint32_t a0, uint32_t a1, uint32_t b0) {
    asm volatile("mma.sync.aligned.m16n8k8.row.col.f32.bf16.bf16.f32 {%0,%1,%2,%3}, {%4,%5}, {%6}, {%0,%1,%2,%3};"
                 : "+f"(c[0]), "+f"(c[1]), "+f"(c[2]), "+f"(c[3]) : "r"(a0), "r"(a1), "r"(b0));
}
__device__ __forceinline__ bool ll_load(const ulonglong2* p, uint32_t& a, uint32_t& b, uint32_t tag) {
    u64 x, y;
    asm volatile("ld.relaxed.gpu.global.v2.b64 {%0, %1}, [%2];" : "=l"(x), "=l"(y) : "l"(p) : "memory");
    a = (uint32_t)x;
    b = (uint32_t)y;
    return ll_ok(x, y, tag);
}

__device__ __forceinline__ void load_wo_frags(uint32_t (&wf)[14][4], uint32_t seg, int lane) {
    const uint32_t row = 4 * ((lane >> 1) & 1) + 2 * ((lane >> 2) & 1) + (lane & 1);
    const uint32_t a = seg + row * 128 + ((((uint32_t)lane >> 3) ^ row) << 4);
#pragma unroll
    for (int x = 0; x < 14; x++) ldsm4t(wf[x], (a ^ ((x & 1) << 6)) + (x >> 1) * 1024);
}
__device__ __forceinline__ void project(float (&y)[7][4], const uint32_t (&wf)[14][4], uint32_t o2, int lane) {
#pragma unroll
    for (int q = 0; q < 4; q++) {
        const uint32_t bq = ((lane >> 2) == 2 * q) ? o2 : 0u;
#pragma unroll
        for (int j = 0; j < 7; j++) {
            const int i = 4 * j + q;
            mma1688(y[j], wf[i >> 1][2 * (i & 1)], wf[i >> 1][2 * (i & 1) + 1], bq);
        }
    }
}

struct L {
    static constexpr int RING = 0;
    static constexpr int SEG = NS * STAGE_BYTES;
    static constexpr int SLOTS = SEG + SEG_BYTES;
    static constexpr int Q0 = SLOTS + W * 2 * SLOT_STRIDE * 4;
    static constexpr int SLOTML = Q0 + 16 * 128 * 8;
    static constexpr int OFIN = SLOTML + W * 16;
    static constexpr int TK = OFIN + 32 * 4;
    static constexpr int BARS = TK + 32 * 4;
    static constexpr int NBARS = 3 * NS + 6 + 8;
    static constexpr int SIZE = BARS + NBARS * 8;
};

__global__ void __launch_bounds__(NTHREADS, 1) fused_decode_kernel(const __grid_constant__ Params p) {
    extern __shared__ __align__(1024) unsigned char smem_raw[];
    static_assert(NS % W == 0 && K0 >= CAP && CAP >= CAP_END && K0 <= NS - 4 && W == 4, "geometry");
    unsigned char* smem = smem_raw;
    const uint32_t sbase = smem_u32(smem);
    const int warp = threadIdx.x >> 5, lane = threadIdx.x & 31;
    const int cta = blockIdx.x;
    const bool has_task = cta < 128;
    const bool isX = has_task && cta >= 64, isY = cta < 64;
    const int slice = cta & 63;

    const uint32_t bar_full = sbase + L::BARS;
    const uint32_t bar_fullv = bar_full + NS * 8;
    const uint32_t bar_empty = bar_fullv + NS * 8;
    const uint32_t bar_wq = bar_empty + NS * 8;
    const uint32_t bar_q = bar_wq + 8;
    const uint32_t bar_q2 = bar_q + 8;
    const uint32_t bar_q3 = bar_q2 + 8;
    const uint32_t bar_ofin = bar_q3 + 8;
    const uint32_t bar_wo = bar_ofin + 8;
    const uint32_t bar_wqdone = bar_wo + 64;
    volatile int* s_tk = reinterpret_cast<volatile int*>(smem + L::TK);
    float* s_slots = reinterpret_cast<float*>(smem + L::SLOTS);
    float* s_slotml = reinterpret_cast<float*>(smem + L::SLOTML);
    float* s_red = reinterpret_cast<float*>(smem + L::SEG);
    uint32_t* s_ofin = reinterpret_cast<uint32_t*>(smem + L::OFIN);
    uint2* s_q0 = reinterpret_cast<uint2*>(smem + L::Q0);

    uint64_t pol = 0;
    auto issue = [&](int s, int t) {
        s_tk[s] = t;
        s_tk[30] = t;
        const uint32_t dst = sbase + L::RING + s * STAGE_BYTES;
        const int b = t >> 15, row = (t & 32767) << 4;
        mbar_expect_tx(bar_full + s * 8, TILE_BYTES);
        tma3d(dst, &p.km[b], row, bar_full + s * 8, pol);
        mbar_expect_tx(bar_fullv + s * 8, TILE_BYTES);
        tma3d(dst + TILE_BYTES, &p.vm[b], row, bar_fullv + s * 8, pol);
    };
    if (threadIdx.x == W * 32) {
        mbar_init(bar_wq, 1);
#pragma unroll
        for (int i = 0; i < K0; i++) { mbar_init(bar_full + i * 8, 1); mbar_init(bar_fullv + i * 8, 1); }
        asm volatile("fence.mbarrier_init.release.cluster;" ::: "memory");
        pol = evict_first_policy();
        if (has_task) {
            mbar_expect_tx(bar_wq, 448 * 128);
#pragma unroll
            for (int i = 0; i < 2; i++)
                asm volatile(
                    "cp.async.bulk.tensor.2d.shared::cluster.global.mbarrier::complete_tx::bytes.L2::cache_hint "
                    "[%0], [%1, {%3, %4}], [%2], %5;" ::"r"(sbase + L::RING + (NS - 4) * STAGE_BYTES + i * 224 * 128),
                    "l"(&p.wqm[cta >> 6]), "r"(bar_wq), "r"((cta & 63) * 64), "r"(i * 224), "l"(pol) : "memory");
        }
#pragma unroll
        for (int i = 0; i < K0; i++) issue(i, cta + G * i);
#pragma unroll
        for (int i = 0; i < L::NBARS; i++)
            if (!(i < K0 || (i >= NS && i < NS + K0) || i == 3 * NS)) mbar_init(bar_full + i * 8, i == L::NBARS - 1 ? W : 1);
        asm volatile("fence.mbarrier_init.release.cluster;" ::: "memory");
    }

    if (warp == W) {
        __syncwarp();
        asm volatile("bar.arrive 2, %0;" ::"n"(NTHREADS) : "memory");
        if (lane == 0) {
            asm volatile("prefetch.tensormap [%0];" ::"l"(&p.km[1]) : "memory");
            asm volatile("prefetch.tensormap [%0];" ::"l"(&p.vm[1]) : "memory");
            asm volatile("prefetch.tensormap [%0];" ::"l"(&p.wom[0]) : "memory");
        }
        pol = evict_first_policy();
        uint32_t ttag;
        asm volatile("ld.relaxed.gpu.global.u32 %0, [%1];" : "=r"(ttag) : "l"(&g_epoch) : "memory");
        int s = K0, t = 0;
        uint32_t ph = 1;
        bool first_lap = has_task;
        while (true) {
            const int cap = (t >= TOTAL - END_ZONE) ? CAP_END : CAP;
            {
                int sd = s - cap;
                uint32_t pd = ph ^ 1;
                if (sd < 0) { sd += NS; pd ^= 1; }
                mbar_wait(bar_full + sd * 8, pd);
            }
            unsigned v = 0;
            if (lane == 0) asm volatile("atom.relaxed.gpu.global.inc.u32 %0, [%1], 0x7fffffff;" : "=r"(v) : "l"(&g_ticket) : "memory");
            mbar_wait(bar_empty + s * 8, ph);
            if (first_lap && s == NS - 4) { mbar_wait(bar_wqdone, 0); first_lap = false; }
            v = __shfl_sync(0xffffffffu, v, 0) - ticket_base(ttag);
            if (v >= (1u << 20)) {
                unsigned n = 0;
                do {
                    __nanosleep(100);
                    if (lane == 0) asm volatile("atom.relaxed.gpu.global.inc.u32 %0, [%1], 0x7fffffff;" : "=r"(v) : "l"(&g_ticket) : "memory");
                    v = __shfl_sync(0xffffffffu, v, 0) - ticket_base(ttag);
                    if (++n > SPIN_LIMIT) __trap();
                } while (v >= (1u << 20));
            }
            t = (int)v + G * K0;
            if (t >= TOTAL) break;
            const uint32_t dst = sbase + L::RING + s * STAGE_BYTES;
            const int b = t >> 15;
            asm volatile(
                "{\n.reg .pred p;\nelect.sync _|p, 0xffffffff;\n"
                "@p st.volatile.shared.u32 [%8], %9;\n"
                "@p st.volatile.shared.u32 [%10], %9;\n"
                "@p mbarrier.arrive.expect_tx.shared::cta.b64 _, [%3], 8192;\n"
                "@p cp.async.bulk.tensor.3d.shared::cluster.global.mbarrier::complete_tx::bytes.L2::cache_hint "
                "[%0], [%1, {%5, %6, %5}], [%3], %7;\n"
                "@p mbarrier.arrive.expect_tx.shared::cta.b64 _, [%4], 8192;\n"
                "@p cp.async.bulk.tensor.3d.shared::cluster.global.mbarrier::complete_tx::bytes.L2::cache_hint "
                "[%11], [%2, {%5, %6, %5}], [%4], %7;\n}"
                ::"r"(dst), "l"(&p.km[b]), "l"(&p.vm[b]), "r"(bar_full + s * 8), "r"(bar_fullv + s * 8), "r"(0),
                  "r"((t & 32767) << 4), "l"(pol), "r"(sbase + L::TK + s * 4), "r"(t), "r"(sbase + L::TK + 30 * 4),
                  "r"(dst + TILE_BYTES) : "memory");
            if (++s == NS) { s = 0; ph ^= 1; }
        }
        if (lane == 0) {
            s_tk[30] = PROG_END;
            s_tk[31] = s;
        }
        __syncwarp();
        if (lane < W) {
            int sj = s + lane;
            uint32_t pj = ph;
            if (sj >= NS) { sj -= NS; pj ^= 1; }
            mbar_wait(bar_empty + sj * 8, pj);
            s_tk[sj] = TOTAL;
            mbar_arrive(bar_full + sj * 8);
        }
        __syncwarp();
        if (isY) {
            mbar_wait(bar_wqdone, 0);
            {
                int sd = s - 2;
                uint32_t pd = ph ^ 1;
                if (sd < 0) { sd += NS; pd ^= 1; }
                mbar_wait(bar_full + sd * 8, pd);
            }
#pragma unroll
            for (int k = 0; k < 8; k++) {
                int ws = s + (k >> 1);
                if (ws >= NS) ws -= NS;
                asm volatile(
                    "{\n.reg .pred p;\nelect.sync _|p, 0xffffffff;\n"
                    "@p mbarrier.arrive.expect_tx.shared::cta.b64 _, [%2], 7168;\n"
                    "@p cp.async.bulk.tensor.3d.shared::cluster.global.mbarrier::complete_tx::bytes.L2::cache_hint "
                    "[%0], [%1, {%3, %4, %3}], [%2], %5;\n}"
                    ::"r"(sbase + L::RING + ws * STAGE_BYTES + (k & 1) * SEG_BYTES), "l"(&p.wom[0]), "r"(bar_wo + k * 8),
                      "r"(0), "r"(k * 512 + slice * 8), "l"(pol) : "memory");
            }
        }
    } else if (warp == W + 1) {
        uint32_t tag;
        asm volatile("ld.relaxed.gpu.global.u32 %0, [%1];" : "=r"(tag) : "l"(&g_epoch) : "memory");
        if (cta == G - 1 && lane == 0)
            asm volatile("st.relaxed.gpu.global.u32 [%0], %1;" ::"l"(&g_ticket), "r"(ticket_base(tag)) : "memory");
        tag += 1;
        auto wait_progress = [&](int target) {
            unsigned n = 0;
            while (s_tk[30] < target) {
                __nanosleep(100);
                if (++n > SPIN_LIMIT) __trap();
            }
        };
        {
            bool synced = false;
#pragma unroll 1
            for (int h = 0; h < 16; h++) {
                if (h == 1) wait_progress(Q_DELAY);
                unsigned n = 0;
                uint32_t qa[4], qb[4];
                while (true) {
                    bool ok = true;
#pragma unroll
                    for (int i = 0; i < 4; i++) ok &= ll_load(g_q + h * 128 + i * 32 + lane, qa[i], qb[i], tag);
                    if (!synced) {
                        asm volatile("bar.sync 2, %0;" ::"n"(NTHREADS) : "memory");
                        if (has_task) mbar_wait(bar_wqdone, 0);
                        synced = true;
                    }
                    if (__all_sync(0xffffffffu, ok)) break;
                    if (++n > SPIN_LIMIT) __trap();
                }
#pragma unroll
                for (int i = 0; i < 4; i++) s_q0[h * 128 + i * 32 + lane] = make_uint2(qa[i], qb[i]);
                __syncwarp();
                if (lane == 0) {
                    if (h == 0) mbar_arrive(bar_q);
                    if (h == 3) mbar_arrive(bar_q2);
                    if (h == 15) mbar_arrive(bar_q3);
                }
            }
        }
        if (has_task) {
            const uint32_t bit = tag & 1u, bitmask = 0u - bit;
            const int qh = slice >> 5;
            const int g = lane >> 2, t4 = lane & 3;
            pol = evict_first_policy();
            float y[7][4];
#pragma unroll
            for (int j = 0; j < 7; j++) { y[j][0] = 0.f; y[j][1] = 0.f; y[j][2] = 0.f; y[j][3] = 0.f; }
            const int h0 = isX ? 8 : 0;
#pragma unroll 1
            for (int h = h0; h < h0 + 8; h++) {
                {
                    uint32_t wf[14][4];
                    if (isX) {
                        wait_progress(h * 4096);
                        if (lane == 0) {
                            asm volatile("fence.proxy.async.shared::cta;" ::: "memory");
                            mbar_expect_tx(bar_wo + (h & 7) * 8, SEG_BYTES);
                            tma3d(sbase + L::SEG, &p.wom[1], (h & 7) * 512 + slice * 8, bar_wo + (h & 7) * 8, pol);
                        }
                        mbar_wait(bar_wo + (h & 7) * 8, 0);
                        load_wo_frags(wf, sbase + L::SEG, lane);
                        __syncwarp();
                    }
                    wait_progress(h < 15 ? (h + 1) * 4096 + MERGE_DELAY : PROG_END);
                    u64 ml[5];
                    uint4 ov[9];
                    const ulonglong2* pml = g_pml + ((h * G + lane) * 2 + qh) * 2;
                    const uint4* pr = g_po + ((size_t)(h * 32 + (slice >> 1)) * G + (lane >> 1)) * 4 + (slice & 1) * 2 + (lane & 1);
                    constexpr int PRS = 16 * 4;
                    const ulonglong2* pml4 = pml + (lane < G - 128 ? 4 * 128 : 0);
                    const uint4* pr8 = pr + (lane < (G - 128) * 2 ? 8 * PRS : 0);
#pragma unroll
                    for (int j = 0; j < 5; j++) ldu64(ml[j], j < 4 ? pml + j * 128 : pml4);
#pragma unroll
                    for (int it = 0; it < 9; it++) ld128(ov[it], it < 8 ? pr + it * PRS : pr8);
                    unsigned n = 0;
                    while (true) {
                        const uint32_t bad = or3(
                            or3(xor_or((uint32_t)(ml[0] >> 32), (uint32_t)(ml[1] >> 32), bitmask),
                                xor_or((uint32_t)(ml[2] >> 32), (uint32_t)(ml[3] >> 32), bitmask),
                                xor_or((uint32_t)(ml[4] >> 32), ov[0].x, bitmask)),
                            or3(xor_or(ov[1].x, ov[2].x, bitmask), xor_or(ov[3].x, ov[4].x, bitmask), xor_or(ov[5].x, ov[6].x, bitmask)),
                            xor_or(ov[7].x, ov[8].x, bitmask));
                        if (__all_sync(0xffffffffu, (bad & 1u) == 0) && (h == 15 || n > 0)) break;
                        if (h != 15) __nanosleep(400);
                        if (++n > SPIN_LIMIT) __trap();
#pragma unroll
                        for (int j = 0; j < 5; j++) ldu64_stale(ml[j], j < 4 ? pml + j * 128 : pml4, bit);
#pragma unroll
                        for (int it = 0; it < 9; it++) ld128_stale(ov[it], it < 8 ? pr + it * PRS : pr8, bit);
                    }
                    float mj[5];
#pragma unroll
                    for (int j = 0; j < 5; j++) mj[j] = __uint_as_float((uint32_t)ml[j]);
                    const float M = warp_max(fmaxf(fmaxf(fmaxf(mj[0], mj[1]), fmaxf(mj[2], mj[3])), mj[4]));
                    float wc[5], Ls = 0.f;
#pragma unroll
                    for (int j = 0; j < 5; j++) {
                        wc[j] = ex2(mj[j] - M);
                        if (j == 4 && lane >= G - 128) wc[j] = 0.f;
                        Ls += wc[j] * __uint_as_float((uint32_t)(ml[j] >> 32));
                    }
                    float a0 = 0.f, a1 = 0.f, a2 = 0.f, a3 = 0.f;
#pragma unroll
                    for (int it = 0; it < 9; it++) {
                        const float wv = __shfl_sync(0xffffffffu, wc[it >> 1], 16 * (it & 1) + (lane >> 1));
                        a0 += wv * __uint_as_float(ov[it].x);
                        a1 += wv * __uint_as_float(ov[it].y);
                        a2 += wv * __uint_as_float(ov[it].z);
                        a3 += wv * __uint_as_float(ov[it].w);
                        if (it == 0) Ls += __shfl_xor_sync(0xffffffffu, Ls, 1);
                    }
                    const bool up = lane & 2;
                    float ax = (up ? a2 : a0) + __shfl_xor_sync(0xffffffffu, up ? a0 : a2, 2);
                    float ay = (up ? a3 : a1) + __shfl_xor_sync(0xffffffffu, up ? a1 : a3, 2);
                    Ls += __shfl_xor_sync(0xffffffffu, Ls, 2);
#pragma unroll
                    for (int o = 4; o <= 16; o <<= 1) {
                        ax += __shfl_xor_sync(0xffffffffu, ax, o);
                        ay += __shfl_xor_sync(0xffffffffu, ay, o);
                        Ls += __shfl_xor_sync(0xffffffffu, Ls, o);
                    }
                    float inv;
                    asm("rcp.approx.ftz.f32 %0, %1;" : "=f"(inv) : "f"(Ls));
                    const uint32_t o2 = pack_bf16(ax * inv, ay * inv);
                    if (isY) {
                        if (lane < 4) s_ofin[h * 4 + lane] = o2;
                        __syncwarp();
                        if (h == 7 && lane == 0) mbar_arrive(bar_ofin);
                    } else {
                        project(y, wf, o2, lane);
                    }
                }
                if (h >= 14) {
                    const uint32_t obit = (h == 15) ? bit : bit ^ 1u;
                    char* dst = reinterpret_cast<char*>(g_ol + ((size_t)(56 + g) * 64 + slice) * 2) + t4 * 8;
#pragma unroll
                    for (int j = 0; j < 7; j++) st64(dst + (size_t)j * 8 * 64 * 32, pt_enc(y[j][0], obit), __float_as_uint(y[j][2]));
                }
            }
            if (cta == 127 && lane == 0) {
                asm volatile("st.relaxed.gpu.global.u32 [%0], %1;" ::"l"(&g_epoch), "r"(tag) : "memory");
            }
        }
    } else {
        uint32_t tag;
        asm volatile("ld.relaxed.gpu.global.u32 %0, [%1];" : "=r"(tag) : "l"(&g_epoch) : "memory");
        const int g = lane >> 2, t4 = lane & 3;
        if (has_task) {
            const int tb = cta >> 6, qs = cta & 63;
            const int r = threadIdx.x >> 3, c8 = threadIdx.x & 7;
            const uint2* xp = reinterpret_cast<const uint2*>(p.x[tb] + 28 * r);
            uint2 xv[7];
#pragma unroll
            for (int i = 0; i < 7; i++)
                asm volatile("ld.global.nc.v2.u32 {%0,%1}, [%2];" : "=r"(xv[i].x), "=r"(xv[i].y) : "l"(xp + i));
            asm volatile("bar.sync 2, %0;" ::"n"(NTHREADS) : "memory");
            mbar_wait(bar_wq, 0);
            const uint4* wv = reinterpret_cast<const uint4*>(smem + L::RING + (NS - 4) * STAGE_BYTES) + 28 * r * 8 + c8;
            float acc[8];
#pragma unroll
            for (int j = 0; j < 8; j++) acc[j] = 0.f;
#pragma unroll
            for (int i = 0; i < 28; i++) {
                const uint32_t xw = (i & 2) ? xv[i >> 2].y : xv[i >> 2].x;
                const float xs = (i & 1) ? bf_hi(xw) : bf_lo(xw);
                const uint4 v = wv[i * 8];
                acc[0] += xs * bf_lo(v.x); acc[1] += xs * bf_hi(v.x);
                acc[2] += xs * bf_lo(v.y); acc[3] += xs * bf_hi(v.y);
                acc[4] += xs * bf_lo(v.z); acc[5] += xs * bf_hi(v.z);
                acc[6] += xs * bf_lo(v.w); acc[7] += xs * bf_hi(v.w);
            }
#pragma unroll
            for (int j = 0; j < 8; j++) {
                acc[j] += __shfl_xor_sync(0xffffffffu, acc[j], 8);
                acc[j] += __shfl_xor_sync(0xffffffffu, acc[j], 16);
            }
            if (lane < 8) {
                float4* d = reinterpret_cast<float4*>(s_red + warp * 64 + lane * 8);
                d[0] = make_float4(acc[0], acc[1], acc[2], acc[3]);
                d[1] = make_float4(acc[4], acc[5], acc[6], acc[7]);
            }
            asm volatile("bar.sync 1, %0;" ::"n"(W * 32) : "memory");
            if (threadIdx.x < 16) {
                const int il = threadIdx.x >> 2;
                float q[4];
#pragma unroll
                for (int k = 0; k < 4; k++) {
                    const int d = 16 * il + 2 * t4 + (k & 1) + 8 * (k >> 1);
                    q[k] = 0.f;
#pragma unroll
                    for (int w = 0; w < W; w++) q[k] += s_red[w * 64 + d];
                }
                ll_store(g_q + ((tb * 16 + (qs >> 2)) * 16 + (qs & 3) * 4 + il) * 4 + t4,
                         pack_bf16(q[0], q[1]), pack_bf16(q[2], q[3]), tag + 1);
            }
            __syncwarp();
            if (lane == 0) mbar_arrive(bar_wqdone);
        } else {
            asm volatile("bar.sync 2, %0;" ::"n"(NTHREADS) : "memory");
        }
        tag += 1;
        const uint32_t bit = tag & 1u;

        float acc[4][4];
#pragma unroll
        for (int i = 0; i < 4; i++) { acc[i][0] = 0.f; acc[i][1] = 0.f; acc[i][2] = 0.f; acc[i][3] = 0.f; }
        float m0 = -INFINITY, m1 = -INFINITY;
        float lacc[4] = {0.f, 0.f, 0.f, 0.f};
        const uint32_t ones[4] = {0x3f803f80u, 0x3f803f80u, 0x3f803f80u, 0x3f803f80u};
        uint32_t qf[16][2];
        int cur = 0;
        const uint32_t krow = (lane & 7) + 8 * ((lane >> 3) & 1), vrow = (lane & 7) + 8 * (lane >> 4);
        const uint32_t koff = krow * 128 + (((lane >> 4) ^ (krow & 7)) << 4);
        const uint32_t voff = TILE_BYTES + vrow * 128 + ((((lane >> 3) & 1) ^ (vrow & 7)) << 4);
        const float SC = 0.0625f * 1.4426950408889634f;
        char* const ydst = reinterpret_cast<char*>(g_ol + ((size_t)(8 * warp + g) * 64 + slice) * 2) + t4 * 8;
        int s = warp;
        uint32_t ph = 0;
        mbar_wait(bar_q, 0);
#pragma unroll
        for (int i = 0; i < 16; i++) {
            const uint2 v = s_q0[((g & 1) * 16 + i) * 4 + t4];
            qf[i][0] = v.x;
            qf[i][1] = v.y;
        }
        while (true) {
            mbar_wait(bar_full + s * 8, ph);
            const int t = s_tk[s];
            const int h = t >> 12;
            if (h != cur) {
                while (cur < h) {
                    float* sl = s_slots + warp * 2 * SLOT_STRIDE + 16 * t4 + 8 * (t4 >> 1) + g;
                    if (lane == 0) *reinterpret_cast<float4*>(s_slotml + warp * 4) = make_float4(m0, lacc[0], m1, lacc[1]);
#pragma unroll
                    for (int j = 0; j < 4; j++) {
                        sl[80 * j] = acc[j][0];
                        sl[80 * j + SLOT_STRIDE] = acc[j][1];
                        sl[80 * j + 8] = acc[j][2];
                        sl[80 * j + 8 + SLOT_STRIDE] = acc[j][3];
                    }
                    uint4* po = g_po + ((size_t)(cur * 32 + 8 * warp + (lane >> 2)) * G + cta) * 4 + (lane & 3);
                    ulonglong2* pml = g_pml + ((cur * G + cta) * 2 + (warp >> 1)) * 2 + lane;
                    asm volatile("bar.sync 1, %0;" ::"n"(W * 32) : "memory");
                    float2 mlw[W];
                    float4 sv[W];
                    float M = -INFINITY;
#pragma unroll
                    for (int w = 0; w < W; w++) {
                        mlw[w] = *reinterpret_cast<const float2*>(s_slotml + w * 4 + (warp & 2));
                        sv[w] = *reinterpret_cast<const float4*>(s_slots + (w * 2 + (warp >> 1)) * SLOT_STRIDE + 160 * (warp & 1) + 4 * lane + (lane & 24));
                        M = fmaxf(M, mlw[w].x);
                    }
                    const float R = (M == -INFINITY) ? 0.f : M;
                    float4 o = make_float4(0.f, 0.f, 0.f, 0.f);
                    float Lw = 0.f;
#pragma unroll
                    for (int w = 0; w < W; w++) {
                        const float f = ex2(mlw[w].x - R);
                        Lw += f * mlw[w].y;
                        o.x += f * sv[w].x; o.y += f * sv[w].y; o.z += f * sv[w].z; o.w += f * sv[w].w;
                    }
                    st128(po, pt_enc(o.x, bit), __float_as_uint(o.y), __float_as_uint(o.z), __float_as_uint(o.w));
                    const bool mlwriter = !(warp & 1) && lane < 2;
                    if (mlwriter) ll_store(pml, __float_as_uint(M), __float_as_uint(M), pt_enc(Lw, bit));
                    if (cur == 13) {
                        st128(po + 2 * 32 * G * 4, bit ^ 1u, 0u, 0u, 0u);
                        if (mlwriter) ll_store(pml + 2 * G * 4, 0u, 0u, bit ^ 1u);
                        if (isY) {
                            st64(ydst, bit ^ 1u, 0u);
                            if (warp < 3) st64(ydst + 4 * 8 * 64 * 32, bit ^ 1u, 0u);
                        }
                    }
#pragma unroll
                    for (int i = 0; i < 4; i++) { acc[i][0] = 0.f; acc[i][1] = 0.f; acc[i][2] = 0.f; acc[i][3] = 0.f; }
                    m0 = -INFINITY; m1 = -INFINITY;
                    lacc[0] = 0.f; lacc[1] = 0.f; lacc[2] = 0.f; lacc[3] = 0.f;
                    cur++;
                    asm volatile("bar.sync 1, %0;" ::"n"(W * 32) : "memory");
                }
                if (h >= 16) break;
                mbar_wait(h > 3 ? bar_q3 : bar_q2, 0);
#pragma unroll
                for (int i = 0; i < 16; i++) {
                    const uint2 v = s_q0[h * 128 + ((g & 1) * 16 + i) * 4 + t4];
                    qf[i][0] = v.x;
                    qf[i][1] = v.y;
                }
            }
            const uint32_t stage = sbase + L::RING + s * STAGE_BYTES;
            float sc[4][4];
#pragma unroll
            for (int c = 0; c < 4; c++) { sc[c][0] = 0.f; sc[c][1] = 0.f; sc[c][2] = 0.f; sc[c][3] = 0.f; }
            const uint32_t kb = stage + koff;
#pragma unroll
            for (int i = 0; i < 16; i++) {
                uint32_t a[4];
                ldsm4(a, (kb ^ ((i & 3) << 5)) + (i >> 2) * 2048);
                mma16816(sc[i & 3], a, qf[i][0], qf[i][1]);
            }
            const float s0 = ((sc[0][0] + sc[1][0]) + (sc[2][0] + sc[3][0])) * SC;
            const float s1 = ((sc[0][1] + sc[1][1]) + (sc[2][1] + sc[3][1])) * SC;
            const float s2 = ((sc[0][2] + sc[1][2]) + (sc[2][2] + sc[3][2])) * SC;
            const float s3 = ((sc[0][3] + sc[1][3]) + (sc[2][3] + sc[3][3])) * SC;
            float n0 = fmaxf(s0, s2), n1 = fmaxf(s1, s3);
            if (__any_sync(0xffffffffu, (n0 > m0) | (n1 > m1))) {
                n0 = fmaxf(warp_max(n0), m0);
                n1 = fmaxf(warp_max(n1), m1);
                const float f0 = ex2(m0 - n0), f1 = ex2(m1 - n1);
                m0 = n0; m1 = n1;
                lacc[0] *= f0; lacc[1] *= f1; lacc[2] *= f0; lacc[3] *= f1;
#pragma unroll
                for (int i = 0; i < 4; i++) { acc[i][0] *= f0; acc[i][1] *= f1; acc[i][2] *= f0; acc[i][3] *= f1; }
            }
            const float p0 = ex2(s0 - m0), p1 = ex2(s1 - m1), p2 = ex2(s2 - m0), p3 = ex2(s3 - m1);
            const uint32_t b0 = movtrans(pack_bf16(p0, p1));
            const uint32_t b1 = movtrans(pack_bf16(p2, p3));
            mma16816(lacc, ones, b0, b1);
            mbar_wait(bar_fullv + s * 8, ph);
            const uint32_t vb = stage + voff;
#pragma unroll
            for (int q = 0; q < 4; q++) {
                const uint32_t c0 = ((g >> 1) == q) ? b0 : 0u, c1 = ((g >> 1) == q) ? b1 : 0u;
#pragma unroll
                for (int j = 0; j < 4; j++) {
                    uint32_t a[4];
                    ldsm4t(a, (vb ^ (q << 5)) + j * 2048);
                    mma16816(acc[j], a, c0, c1);
                }
            }
            __syncwarp();
            if (lane == 0) mbar_arrive(bar_empty + s * 8);
            s += W;
            if (s >= NS) { s -= NS; ph ^= 1; }
        }

        if (isY) {
            mbar_wait(bar_ofin, 0);
            float y[7][4];
#pragma unroll
            for (int j = 0; j < 7; j++) { y[j][0] = 0.f; y[j][1] = 0.f; y[j][2] = 0.f; y[j][3] = 0.f; }
            float2* red = reinterpret_cast<float2*>(s_red);
#pragma unroll 1
            for (int k = warp; k < 8; k += W) {
                const uint32_t o2 = s_ofin[k * 4 + t4];
                int ws = s_tk[31] + (k >> 1);
                if (ws >= NS) ws -= NS;
                mbar_wait(bar_wo + k * 8, 0);
                uint32_t wf[14][4];
                load_wo_frags(wf, sbase + L::RING + ws * STAGE_BYTES + (k & 1) * SEG_BYTES, lane);
                project(y, wf, o2, lane);
            }
#pragma unroll
            for (int j = 0; j < 7; j++) red[(warp * 7 + j) * 32 + lane] = make_float2(y[j][0], y[j][2]);
            asm volatile("bar.sync 1, %0;" ::"n"(W * 32) : "memory");
#pragma unroll
            for (int jj = 0; jj < 2; jj++) {
                const int j = warp + 4 * jj;
                if (j < 7) {
                    float vx = 0.f, vy = 0.f;
#pragma unroll
                    for (int w = 0; w < W; w++) {
                        const float2 v = red[(w * 7 + j) * 32 + lane];
                        vx += v.x;
                        vy += v.y;
                    }
                    st64(ydst + jj * 4 * 8 * 64 * 32, pt_enc(vx, bit), __float_as_uint(vy));
                }
            }
        }
        if (isX && slice < 56 && !(warp & 1)) {
            const bool fb = warp < 2;
            const uint32_t bitmask = 0u - bit;
            const uint4* src = g_ol + (size_t)((fb ? 56 : 0) + slice) * 64 * 2 + lane;
            const int et = 2 * (lane & 1) + ((lane >> 1) & 1), es = (lane >> 2) & 1;
            const int col = (fb ? DM : 0) + 64 * (slice >> 3) + 16 * et + 8 * es + (slice & 7);
            __nv_bfloat16* dst = p.out + col;
            unsigned n = 0;
            while (true) {
                uint4 v[4];
#pragma unroll
                for (int i = 0; i < 4; i++) ld2x64(v[i], src + i * 32);
                const uint32_t bad = or3(xor_or(v[0].x, v[0].z, bitmask), xor_or(v[1].x, v[1].z, bitmask),
                                         xor_or(v[2].x, v[2].z, bitmask)) | xor_or(v[3].x, v[3].z, bitmask);
                const bool done = __all_sync(0xffffffffu, (bad & 1u) == 0);
                const float a0 = (__uint_as_float(v[0].x) + __uint_as_float(v[1].x)) + (__uint_as_float(v[2].x) + __uint_as_float(v[3].x));
                const float a1 = (__uint_as_float(v[0].y) + __uint_as_float(v[1].y)) + (__uint_as_float(v[2].y) + __uint_as_float(v[3].y));
                const float a2 = (__uint_as_float(v[0].z) + __uint_as_float(v[1].z)) + (__uint_as_float(v[2].z) + __uint_as_float(v[3].z));
                const float a3 = (__uint_as_float(v[0].w) + __uint_as_float(v[1].w)) + (__uint_as_float(v[2].w) + __uint_as_float(v[3].w));
                if (done || n == 0) {
                    const bool u1 = lane & 2, u2 = lane & 4;
                    const float bx = (u1 ? a2 : a0) + __shfl_xor_sync(0xffffffffu, u1 ? a0 : a2, 2);
                    const float by = (u1 ? a3 : a1) + __shfl_xor_sync(0xffffffffu, u1 ? a1 : a3, 2);
                    float c = (u2 ? by : bx) + __shfl_xor_sync(0xffffffffu, u2 ? bx : by, 4);
                    c += __shfl_xor_sync(0xffffffffu, c, 8);
                    c += __shfl_xor_sync(0xffffffffu, c, 16);
                    if (done && lane < 8) *dst = __float2bfloat16(c);
                    if (done) break;
                }
                if (++n > SPIN_LIMIT) __trap();
            }
        }
    }
}

constexpr int FB_SPLIT = 64;
__device__ float g_fq[2 * 4096];
__device__ float g_fp[16 * FB_SPLIT * 8 * 2 * 264];

__global__ void fb_q_kernel(const __nv_bfloat16* x, const __nv_bfloat16* wq, int b) {
    const int n = blockIdx.x * blockDim.x + threadIdx.x;
    float a = 0.f;
    for (int k = 0; k < DM; k++) a += __bfloat162float(x[k]) * __bfloat162float(wq[(size_t)k * 4096 + n]);
    g_fq[b * 4096 + n] = __bfloat162float(__float2bfloat16(a));
}
__global__ void fb_attn_kernel(const uint4* k, const uint4* v, int b) {
    const int hk = blockIdx.y, warp = threadIdx.x >> 5, lane = threadIdx.x & 31;
    float q[2][8], o[2][8], m[2] = {-INFINITY, -INFINITY}, l[2] = {0.f, 0.f};
    for (int h = 0; h < 2; h++)
        for (int j = 0; j < 8; j++) { q[h][j] = g_fq[b * 4096 + (hk * 2 + h) * 256 + lane * 8 + j]; o[h][j] = 0.f; }
    const int n = 65536 / FB_SPLIT / 8;
    const size_t row0 = (size_t)hk * 65536 + (size_t)(blockIdx.x * 8 + warp) * n;
    for (int i = 0; i < n; i++) {
        const uint4 kk = k[(row0 + i) * 32 + lane], vv = v[(row0 + i) * 32 + lane];
        const float kf[8] = {bf_lo(kk.x), bf_hi(kk.x), bf_lo(kk.y), bf_hi(kk.y), bf_lo(kk.z), bf_hi(kk.z), bf_lo(kk.w), bf_hi(kk.w)};
        const float vf[8] = {bf_lo(vv.x), bf_hi(vv.x), bf_lo(vv.y), bf_hi(vv.y), bf_lo(vv.z), bf_hi(vv.z), bf_lo(vv.w), bf_hi(vv.w)};
#pragma unroll
        for (int h = 0; h < 2; h++) {
            float s = 0.f;
#pragma unroll
            for (int j = 0; j < 8; j++) s += q[h][j] * kf[j];
            for (int d = 16; d >= 1; d >>= 1) s += __shfl_xor_sync(0xffffffffu, s, d);
            s *= 0.0625f * 1.4426950408889634f;
            const float mn = fmaxf(m[h], s), f = ex2(m[h] - mn), pr = ex2(s - mn);
            m[h] = mn;
            l[h] = l[h] * f + pr;
#pragma unroll
            for (int j = 0; j < 8; j++) o[h][j] = o[h][j] * f + pr * vf[j];
        }
    }
    for (int h = 0; h < 2; h++) {
        float* d = g_fp + ((((size_t)(b * 8 + hk) * FB_SPLIT + blockIdx.x) * 8 + warp) * 2 + h) * 264;
        for (int j = 0; j < 8; j++) d[lane * 8 + j] = o[h][j];
        if (lane == 0) { d[256] = m[h]; d[257] = l[h]; }
    }
}
__global__ void fb_merge_kernel() {
    const int hq = blockIdx.x;
    const float* base = g_fp + ((size_t)(hq >> 1) * FB_SPLIT * 8 * 2 + (hq & 1)) * 264;
    float M = -INFINITY, Ls = 0.f, a = 0.f;
    for (int i = 0; i < FB_SPLIT * 8; i++) M = fmaxf(M, base[(size_t)i * 528 + 256]);
    for (int i = 0; i < FB_SPLIT * 8; i++) {
        const float w = ex2(base[(size_t)i * 528 + 256] - M);
        Ls += w * base[(size_t)i * 528 + 257];
        a += w * base[(size_t)i * 528 + threadIdx.x];
    }
    g_fq[hq * 256 + threadIdx.x] = __bfloat162float(__float2bfloat16(a / Ls));
}
__global__ void fb_out_kernel(const __nv_bfloat16* wo, __nv_bfloat16* out, int b) {
    const int n = blockIdx.x * 64 + threadIdx.x;
    float a = 0.f;
    for (int k = 0; k < 4096; k++) a += g_fq[b * 4096 + k] * __bfloat162float(wo[(size_t)k * DM + n]);
    out[b * DM + n] = __float2bfloat16(a);
}

typedef CUresult (*EncodeFn)(CUtensorMap*, CUtensorMapDataType, cuuint32_t, void*, const cuuint64_t*, const cuuint64_t*,
                             const cuuint32_t*, const cuuint32_t*, CUtensorMapInterleave, CUtensorMapSwizzle,
                             CUtensorMapL2promotion, CUtensorMapFloatOOBfill);

void encode_kv(EncodeFn enc, CUtensorMap* m, const void* ptr) {
    cuuint64_t gd[3] = {64, 8ull * 65536ull, 4};
    cuuint64_t gs[2] = {512, 128};
    cuuint32_t box[3] = {64, 16, 4};
    cuuint32_t es[3] = {1, 1, 1};
    enc(m, CU_TENSOR_MAP_DATA_TYPE_BFLOAT16, 3, const_cast<void*>(ptr), gd, gs, box, es, CU_TENSOR_MAP_INTERLEAVE_NONE,
        CU_TENSOR_MAP_SWIZZLE_128B, CU_TENSOR_MAP_L2_PROMOTION_L2_256B, CU_TENSOR_MAP_FLOAT_OOB_FILL_NONE);
}

void encode_wo(EncodeFn enc, CUtensorMap* m, const void* ptr) {
    cuuint64_t gd[3] = {64, 4096, 7};
    cuuint64_t gs[2] = {DM * 2, 128};
    cuuint32_t box[3] = {64, 8, 7};
    cuuint32_t es[3] = {1, 1, 1};
    enc(m, CU_TENSOR_MAP_DATA_TYPE_BFLOAT16, 3, const_cast<void*>(ptr), gd, gs, box, es, CU_TENSOR_MAP_INTERLEAVE_NONE,
        CU_TENSOR_MAP_SWIZZLE_128B, CU_TENSOR_MAP_L2_PROMOTION_L2_128B, CU_TENSOR_MAP_FLOAT_OOB_FILL_NONE);
}

void encode_wq(EncodeFn enc, CUtensorMap* m, const void* ptr) {
    cuuint64_t gd[2] = {4096, 448};
    cuuint64_t gs[1] = {8192};
    cuuint32_t box[2] = {64, 224};
    cuuint32_t es[2] = {1, 1};
    enc(m, CU_TENSOR_MAP_DATA_TYPE_BFLOAT16, 2, const_cast<void*>(ptr), gd, gs, box, es, CU_TENSOR_MAP_INTERLEAVE_NONE,
        CU_TENSOR_MAP_SWIZZLE_NONE, CU_TENSOR_MAP_L2_PROMOTION_L2_128B, CU_TENSOR_MAP_FLOAT_OOB_FILL_NONE);
}

}

extern "C" void kernel_launch(void* const* d_in, const int* in_sizes, int n_in, void* d_out, int out_size) {
    (void)in_sizes; (void)n_in; (void)out_size;
    static EncodeFn enc = nullptr;
    static int mode = -1;
    if (mode < 0) {
        cudaDriverEntryPointQueryResult qr;
        void* fn = nullptr;
        cudaGetDriverEntryPoint("cuTensorMapEncodeTiled", &fn, cudaEnableDefault, &qr);
        enc = (EncodeFn)fn;
        int dev = 0, sms = 0, occ = 0;
        cudaGetDevice(&dev);
        cudaDeviceGetAttribute(&sms, cudaDevAttrMultiProcessorCount, dev);
        const bool attr_ok =
            cudaFuncSetAttribute(fused_decode_kernel, cudaFuncAttributeMaxDynamicSharedMemorySize, L::SIZE) == cudaSuccess;
        if (attr_ok) cudaOccupancyMaxActiveBlocksPerMultiprocessor(&occ, fused_decode_kernel, NTHREADS, L::SIZE);
        mode = (enc != nullptr && attr_ok && sms * occ >= G) ? 1 : 0;
        (void)cudaGetLastError();
    }
    if (mode == 1) {
        Params p;
        for (int b = 0; b < 2; b++) {
            p.x[b] = (const __nv_bfloat16*)d_in[5 * b + 0];
            encode_kv(enc, &p.km[b], d_in[5 * b + 1]);
            encode_kv(enc, &p.vm[b], d_in[5 * b + 2]);
            encode_wq(enc, &p.wqm[b], d_in[5 * b + 3]);
            encode_wo(enc, &p.wom[b], d_in[5 * b + 4]);
        }
        p.out = (__nv_bfloat16*)d_out;
        fused_decode_kernel<<<G, NTHREADS, L::SIZE>>>(p);
    } else {
        for (int b = 0; b < 2; b++) {
            fb_q_kernel<<<16, 256>>>((const __nv_bfloat16*)d_in[5 * b], (const __nv_bfloat16*)d_in[5 * b + 3], b);
            fb_attn_kernel<<<dim3(FB_SPLIT, 8), 256>>>((const uint4*)d_in[5 * b + 1], (const uint4*)d_in[5 * b + 2], b);
        }
        fb_merge_kernel<<<32, 256>>>();
        for (int b = 0; b < 2; b++)
            fb_out_kernel<<<7, 64>>>((const __nv_bfloat16*)d_in[5 * b + 4], (__nv_bfloat16*)d_out, b);
    }
}
```

```cpp
#include <cuda_runtime.h>
#include <cuda_bf16.h>
#include <cuda.h>
#include <stdint.h>

namespace {

constexpr int G = 132;
constexpr int W = 4;
constexpr int NTHREADS = (W + 2) * 32;
constexpr int TILE_BYTES = 8192;
constexpr int STAGE_BYTES = 2 * TILE_BYTES;
constexpr int TOTAL = 65536;
constexpr int DM = 448;
constexpr int SEG_BYTES = 8 * DM * 2;
constexpr int SLOT_STRIDE = 320;
constexpr int PROG_END = 1 << 30;
constexpr int NS = 12;
constexpr int K0 = 2;
constexpr int Q_DELAY = 1500;
constexpr int MERGE_DELAY = 2500;
constexpr int CAP = 4, CAP_END = 3;
constexpr int END_ZONE = 1000;
constexpr unsigned SPIN_LIMIT = 1u << 22;

struct Params {
    const __nv_bfloat16* x[2];
    __nv_bfloat16* out;
    CUtensorMap km[2];
    CUtensorMap vm[2];
    CUtensorMap wqm[2];
    CUtensorMap wom[2];
};

typedef unsigned long long u64;

__device__ unsigned int g_epoch;
__device__ unsigned int g_ticket;
__device__ ulonglong2 g_q[16 * 2 * 16 * 4];
__device__ uint4 g_po[16 * 32 * G * 4];
__device__ ulonglong2 g_pml[16 * G * 2 * 2];
__device__ uint4 g_ol[2 * 56 * 64 * 2];

__device__ __forceinline__ uint32_t smem_u32(const void* p) { return (uint32_t)__cvta_generic_to_shared(p); }
__device__ __forceinline__ void mbar_init(uint32_t bar, uint32_t cnt) {
    asm volatile("mbarrier.init.shared::cta.b64 [%0], %1;" ::"r"(bar), "r"(cnt) : "memory");
}
__device__ __forceinline__ void mbar_expect_tx(uint32_t bar, uint32_t bytes) {
    asm volatile("mbarrier.arrive.expect_tx.shared::cta.b64 _, [%0], %1;" ::"r"(bar), "r"(bytes) : "memory");
}
__device__ __forceinline__ void mbar_arrive(uint32_t bar) {
    asm volatile("mbarrier.arrive.shared::cta.b64 _, [%0];" ::"r"(bar) : "memory");
}
__device__ __forceinline__ bool mbar_try(uint32_t bar, uint32_t parity) {
    uint32_t ok;
    asm volatile("{\n.reg .pred p;\nmbarrier.try_wait.parity.shared::cta.b64 p, [%1], %2;\nselp.u32 %0, 1, 0, p;\n}"
                 : "=r"(ok) : "r"(bar), "r"(parity) : "memory");
    return ok != 0;
}
__device__ __forceinline__ void mbar_wait(uint32_t bar, uint32_t parity) {
    unsigned n = 0;
    while (!mbar_try(bar, parity)) {
        if (++n > SPIN_LIMIT) __trap();
    }
}
__device__ __forceinline__ void tma3d(uint32_t dst, const CUtensorMap* m, int row, uint32_t bar, uint64_t pol) {
    asm volatile(
        "cp.async.bulk.tensor.3d.shared::cluster.global.mbarrier::complete_tx::bytes.L2::cache_hint "
        "[%0], [%1, {%3, %4, %3}], [%2], %5;" ::"r"(dst), "l"(m), "r"(bar), "r"(0), "r"(row), "l"(pol)
        : "memory");
}
__device__ __forceinline__ uint64_t evict_first_policy() {
    uint64_t pol;
    asm volatile("createpolicy.fractional.L2::evict_first.b64 %0, 1.0;" : "=l"(pol));
    return pol;
}
__device__ __forceinline__ void ldsm4(uint32_t (&r)[4], uint32_t addr) {
    asm volatile("ldmatrix.sync.aligned.m8n8.x4.shared.b16 {%0,%1,%2,%3}, [%4];"
                 : "=r"(r[0]), "=r"(r[1]), "=r"(r[2]), "=r"(r[3]) : "r"(addr) : "memory");
}
__device__ __forceinline__ void ldsm4t(uint32_t (&r)[4], uint32_t addr) {
    asm volatile("ldmatrix.sync.aligned.m8n8.x4.trans.shared.b16 {%0,%1,%2,%3}, [%4];"
                 : "=r"(r[0]), "=r"(r[1]), "=r"(r[2]), "=r"(r[3]) : "r"(addr) : "memory");
}
__device__ __forceinline__ void mma16816(float (&c)[4], const uint32_t (&a)[4], uint32_t b0, uint32_t b1) {
    asm volatile("mma.sync.aligned.m16n8k16.row.col.f32.bf16.bf16.f32 {%0,%1,%2,%3}, {%4,%5,%6,%7}, {%8,%9}, {%0,%1,%2,%3};"
                 : "+f"(c[0]), "+f"(c[1]), "+f"(c[2]), "+f"(c[3])
                 : "r"(a[0]), "r"(a[1]), "r"(a[2]), "r"(a[3]), "r"(b0), "r"(b1));
}
__device__ __forceinline__ uint32_t movtrans(uint32_t a) {
    uint32_t d;
    asm volatile("movmatrix.sync.aligned.m8n8.trans.b16 %0, %1;" : "=r"(d) : "r"(a));
    return d;
}
__device__ __forceinline__ float ex2(float x) {
    float y;
    asm("ex2.approx.ftz.f32 %0, %1;" : "=f"(y) : "f"(x));
    return y;
}
__device__ __forceinline__ uint32_t pack_bf16(float lo, float hi) {
    uint32_t d;
    asm("cvt.rn.bf16x2.f32 %0, %1, %2;" : "=r"(d) : "f"(hi), "f"(lo));
    return d;
}
__device__ __forceinline__ float bf_lo(uint32_t v) { return __uint_as_float(v << 16); }
__device__ __forceinline__ float bf_hi(uint32_t v) { return __uint_as_float(v & 0xffff0000u); }
__device__ __forceinline__ float warp_max(float v) {
    int k = __float_as_int(v);
    k ^= (k >> 31) & 0x7fffffff;
    k = __reduce_max_sync(0xffffffffu, k);
    k ^= (k >> 31) & 0x7fffffff;
    return __int_as_float(k);
}

__device__ __forceinline__ u64 ll_word(uint32_t v, uint32_t tag) { return ((u64)tag << 32) | v; }
__device__ __forceinline__ void ll_store(ulonglong2* p, uint32_t a, uint32_t b, uint32_t tag) {
    asm volatile("st.relaxed.gpu.global.v2.b64 [%0], {%1, %2};" ::"l"(p), "l"(ll_word(a, tag)), "l"(ll_word(b, tag)) : "memory");
}
__device__ __forceinline__ bool ll_ok(u64 x, u64 y, uint32_t tag) {
    return ((uint32_t)(x >> 32) == tag) & ((uint32_t)(y >> 32) == tag);
}
__device__ __forceinline__ uint32_t pt_enc(float v, uint32_t bit) { return (__float_as_uint(v) & ~1u) | bit; }
__device__ __forceinline__ uint32_t xor_or(uint32_t a, uint32_t b, uint32_t m) {
    uint32_t d;
    asm("lop3.b32 %0, %1, %2, %3, 0x7e;" : "=r"(d) : "r"(a), "r"(b), "r"(m));
    return d;
}
__device__ __forceinline__ uint32_t or3(uint32_t a, uint32_t b, uint32_t c) {
    uint32_t d;
    asm("lop3.b32 %0, %1, %2, %3, 0xfe;" : "=r"(d) : "r"(a), "r"(b), "r"(c));
    return d;
}
__device__ __forceinline__ void st128(uint4* p, uint32_t a, uint32_t b, uint32_t c, uint32_t d) {
    asm volatile("{\n.reg .b128 t;\n.reg .b64 lo, hi;\nmov.b64 lo, {%1, %2};\nmov.b64 hi, {%3, %4};\nmov.b128 t, {lo, hi};\n"
                 "st.relaxed.gpu.global.b128 [%0], t;\n}" ::"l"(p), "r"(a), "r"(b), "r"(c), "r"(d) : "memory");
}
__device__ __forceinline__ void ld128(uint4& v, const uint4* p) {
    asm volatile("{\n.reg .b128 t;\n.reg .b64 lo, hi;\nld.relaxed.gpu.global.b128 t, [%4];\nmov.b128 {lo, hi}, t;\n"
                 "mov.b64 {%0, %1}, lo;\nmov.b64 {%2, %3}, hi;\n}"
                 : "=r"(v.x), "=r"(v.y), "=r"(v.z), "=r"(v.w) : "l"(p) : "memory");
}
__device__ __forceinline__ void ld128_stale(uint4& v, const uint4* p, uint32_t bit) {
    asm volatile("{\n.reg .pred p;\n.reg .b32 u;\n.reg .b128 t;\n.reg .b64 lo, hi;\nand.b32 u, %0, 1;\nsetp.ne.u32 p, u, %5;\n"
                 "mov.b64 lo, {%0, %1};\nmov.b64 hi, {%2, %3};\nmov.b128 t, {lo, hi};\n"
                 "@p ld.relaxed.gpu.global.b128 t, [%4];\nmov.b128 {lo, hi}, t;\nmov.b64 {%0, %1}, lo;\nmov.b64 {%2, %3}, hi;\n}"
                 : "+r"(v.x), "+r"(v.y), "+r"(v.z), "+r"(v.w) : "l"(p), "r"(bit) : "memory");
}
__device__ __forceinline__ void st64(void* p, uint32_t a, uint32_t b) {
    asm volatile("{\n.reg .b64 t;\nmov.b64 t, {%1, %2};\nst.relaxed.gpu.global.b64 [%0], t;\n}" ::"l"(p), "r"(a), "r"(b) : "memory");
}
__device__ __forceinline__ void ld2x64(uint4& v, const uint4* p) {
    asm volatile("{\n.reg .b64 lo, hi;\nld.relaxed.gpu.global.v2.b64 {lo, hi}, [%4];\nmov.b64 {%0, %1}, lo;\nmov.b64 {%2, %3}, hi;\n}"
                 : "=r"(v.x), "=r"(v.y), "=r"(v.z), "=r"(v.w) : "l"(p) : "memory");
}
__device__ __forceinline__ void ldu64(u64& v, const void* p) {
    asm volatile("ld.relaxed.gpu.global.b64 %0, [%1];" : "=l"(v) : "l"(p) : "memory");
}
__device__ __forceinline__ void ldu64_stale(u64& v, const void* p, uint32_t bit) {
    asm volatile("{\n.reg .pred p;\n.reg .b32 a, b;\nmov.b64 {a, b}, %0;\nand.b32 b, b, 1;\nsetp.ne.u32 p, b, %2;\n"
                 "@p ld.relaxed.gpu.global.b64 %0, [%1];\n}" : "+l"(v) : "l"(p), "r"(bit) : "memory");
}
__device__ __forceinline__ void mma1688(float (&c)[4], uint32_t a0, uint32_t a1, uint32_t b0) {
    asm volatile("mma.sync.aligned.m16n8k8.row.col.f32.bf16.bf16.f32 {%0,%1,%2,%3}, {%4,%5}, {%6}, {%0,%1,%2,%3};"
                 : "+f"(c[0]), "+f"(c[1]), "+f"(c[2]), "+f"(c[3]) : "r"(a0), "r"(a1), "r"(b0));
}
__device__ __forceinline__ bool ll_load(const ulonglong2* p, uint32_t& a, uint32_t& b, uint32_t tag) {
    u64 x, y;
    asm volatile("ld.relaxed.gpu.global.v2.b64 {%0, %1}, [%2];" : "=l"(x), "=l"(y) : "l"(p) : "memory");
    a = (uint32_t)x;
    b = (uint32_t)y;
    return ll_ok(x, y, tag);
}

__device__ __forceinline__ void load_wo_frags(uint32_t (&wf)[14][4], uint32_t seg, int lane) {
    const uint32_t row = 4 * ((lane >> 1) & 1) + 2 * ((lane >> 2) & 1) + (lane & 1);
    const uint32_t a = seg + row * 128 + ((((uint32_t)lane >> 3) ^ row) << 4);
#pragma unroll
    for (int x = 0; x < 14; x++) ldsm4t(wf[x], (a ^ ((x & 1) << 6)) + (x >> 1) * 1024);
}
__device__ __forceinline__ void project(float (&y)[7][4], const uint32_t (&wf)[14][4], uint32_t o2, int lane) {
#pragma unroll
    for (int q = 0; q < 4; q++) {
        const uint32_t bq = ((lane >> 2) == 2 * q) ? o2 : 0u;
#pragma unroll
        for (int j = 0; j < 7; j++) {
            const int i = 4 * j + q;
            mma1688(y[j], wf[i >> 1][2 * (i & 1)], wf[i >> 1][2 * (i & 1) + 1], bq);
        }
    }
}

struct L {
    static constexpr int RING = 0;
    static constexpr int SEG = NS * STAGE_BYTES;
    static constexpr int SLOTS = SEG + SEG_BYTES;
    static constexpr int Q0 = SLOTS + W * 2 * SLOT_STRIDE * 4;
    static constexpr int SLOTML = Q0 + 16 * 128 * 8;
    static constexpr int OFIN = SLOTML + W * 16;
    static constexpr int TK = OFIN + 32 * 4;
    static constexpr int BARS = TK + 32 * 4;
    static constexpr int NBARS = 3 * NS + 6 + 8;
    static constexpr int SIZE = BARS + NBARS * 8;
};

__global__ void __launch_bounds__(NTHREADS, 1) fused_decode_kernel(const __grid_constant__ Params p) {
    extern __shared__ __align__(1024) unsigned char smem_raw[];
    static_assert(NS % W == 0 && K0 >= 2 && K0 <= NS - 4 && W == 4, "geometry");
    unsigned char* smem = smem_raw;
    const uint32_t sbase = smem_u32(smem);
    const int warp = threadIdx.x >> 5, lane = threadIdx.x & 31;
    const int cta = blockIdx.x;
    const bool has_task = cta < 128;
    const bool isX = has_task && cta >= 64, isY = cta < 64;
    const int slice = cta & 63;

    const uint32_t bar_full = sbase + L::BARS;
    const uint32_t bar_fullv = bar_full + NS * 8;
    const uint32_t bar_empty = bar_fullv + NS * 8;
    const uint32_t bar_wq = bar_empty + NS * 8;
    const uint32_t bar_q = bar_wq + 8;
    const uint32_t bar_q2 = bar_q + 8;
    const uint32_t bar_q3 = bar_q2 + 8;
    const uint32_t bar_ofin = bar_q3 + 8;
    const uint32_t bar_wo = bar_ofin + 8;
    const uint32_t bar_wqdone = bar_wo + 64;
    volatile int* s_tk = reinterpret_cast<volatile int*>(smem + L::TK);
    float* s_slots = reinterpret_cast<float*>(smem + L::SLOTS);
    float* s_slotml = reinterpret_cast<float*>(smem + L::SLOTML);
    float* s_red = reinterpret_cast<float*>(smem + L::SEG);
    uint32_t* s_ofin = reinterpret_cast<uint32_t*>(smem + L::OFIN);
    uint2* s_q0 = reinterpret_cast<uint2*>(smem + L::Q0);

    uint64_t pol = 0;
    auto issue = [&](int s, int t) {
        s_tk[s] = t;
        s_tk[30] = t;
        const uint32_t dst = sbase + L::RING + s * STAGE_BYTES;
        const int b = t >> 15, row = (t & 32767) << 4;
        mbar_expect_tx(bar_full + s * 8, TILE_BYTES);
        tma3d(dst, &p.km[b], row, bar_full + s * 8, pol);
        mbar_expect_tx(bar_fullv + s * 8, TILE_BYTES);
        tma3d(dst + TILE_BYTES, &p.vm[b], row, bar_fullv + s * 8, pol);
    };
    if (threadIdx.x == W * 32) {
        mbar_init(bar_wq, 1);
#pragma unroll
        for (int i = 0; i < K0; i++) { mbar_init(bar_full + i * 8, 1); mbar_init(bar_fullv + i * 8, 1); }
        asm volatile("fence.mbarrier_init.release.cluster;" ::: "memory");
        pol = evict_first_policy();
        if (has_task) {
            mbar_expect_tx(bar_wq, 448 * 128);
#pragma unroll
            for (int i = 0; i < 2; i++)
                asm volatile(
                    "cp.async.bulk.tensor.2d.shared::cluster.global.mbarrier::complete_tx::bytes.L2::cache_hint "
                    "[%0], [%1, {%3, %4}], [%2], %5;" ::"r"(sbase + L::RING + (NS - 4) * STAGE_BYTES + i * 224 * 128),
                    "l"(&p.wqm[cta >> 6]), "r"(bar_wq), "r"((cta & 63) * 64), "r"(i * 224), "l"(pol) : "memory");
        }
#pragma unroll
        for (int i = 0; i < K0; i++) issue(i, cta + G * i);
#pragma unroll
        for (int i = 0; i < L::NBARS; i++)
            if (!(i < K0 || (i >= NS && i < NS + K0) || i == 3 * NS)) mbar_init(bar_full + i * 8, i == L::NBARS - 1 ? W : 1);
        asm volatile("fence.mbarrier_init.release.cluster;" ::: "memory");
    }

    if (warp == W) {
        __syncwarp();
        asm volatile("bar.arrive 2, %0;" ::"n"(NTHREADS) : "memory");
        if (lane == 0) {
            asm volatile("prefetch.tensormap [%0];" ::"l"(&p.km[1]) : "memory");
            asm volatile("prefetch.tensormap [%0];" ::"l"(&p.vm[1]) : "memory");
            asm volatile("prefetch.tensormap [%0];" ::"l"(&p.wom[0]) : "memory");
        }
        pol = evict_first_policy();
        int s = K0, cnt = K0, t = 0;
        uint32_t ph = 1;
        bool first_lap = has_task;
        while (true) {
            const int cap = (t >= TOTAL - END_ZONE) ? CAP_END : CAP;
            if (cnt >= cap) {
                int sd = s - cap;
                uint32_t pd = ph ^ 1;
                if (sd < 0) { sd += NS; pd ^= 1; }
                mbar_wait(bar_full + sd * 8, pd);
            }
            cnt++;
            unsigned v = 0;
            if (lane == 0) asm volatile("atom.relaxed.gpu.global.inc.u32 %0, [%1], 0x7fffffff;" : "=r"(v) : "l"(&g_ticket) : "memory");
            mbar_wait(bar_empty + s * 8, ph);
            if (first_lap && s == NS - 4) { mbar_wait(bar_wqdone, 0); first_lap = false; }
            t = (int)__shfl_sync(0xffffffffu, v, 0) + G * K0;
            if (t >= TOTAL) break;
            const uint32_t dst = sbase + L::RING + s * STAGE_BYTES;
            const int b = t >> 15;
            asm volatile(
                "{\n.reg .pred p;\nelect.sync _|p, 0xffffffff;\n"
                "@p st.volatile.shared.u32 [%8], %9;\n"
                "@p st.volatile.shared.u32 [%10], %9;\n"
                "@p mbarrier.arrive.expect_tx.shared::cta.b64 _, [%3], 8192;\n"
                "@p cp.async.bulk.tensor.3d.shared::cluster.global.mbarrier::complete_tx::bytes.L2::cache_hint "
                "[%0], [%1, {%5, %6, %5}], [%3], %7;\n"
                "@p mbarrier.arrive.expect_tx.shared::cta.b64 _, [%4], 8192;\n"
                "@p cp.async.bulk.tensor.3d.shared::cluster.global.mbarrier::complete_tx::bytes.L2::cache_hint "
                "[%11], [%2, {%5, %6, %5}], [%4], %7;\n}"
                ::"r"(dst), "l"(&p.km[b]), "l"(&p.vm[b]), "r"(bar_full + s * 8), "r"(bar_fullv + s * 8), "r"(0),
                  "r"((t & 32767) << 4), "l"(pol), "r"(sbase + L::TK + s * 4), "r"(t), "r"(sbase + L::TK + 30 * 4),
                  "r"(dst + TILE_BYTES) : "memory");
            if (++s == NS) { s = 0; ph ^= 1; }
        }
        if (lane == 0) {
            s_tk[30] = PROG_END;
            s_tk[31] = s;
        }
        __syncwarp();
        if (lane < W) {
            int sj = s + lane;
            uint32_t pj = ph;
            if (sj >= NS) { sj -= NS; pj ^= 1; }
            mbar_wait(bar_empty + sj * 8, pj);
            s_tk[sj] = TOTAL;
            mbar_arrive(bar_full + sj * 8);
        }
        __syncwarp();
        if (isY) {
            mbar_wait(bar_wqdone, 0);
            {
                int sd = s - 2;
                uint32_t pd = ph ^ 1;
                if (sd < 0) { sd += NS; pd ^= 1; }
                mbar_wait(bar_full + sd * 8, pd);
            }
#pragma unroll
            for (int k = 0; k < 8; k++) {
                int ws = s + (k >> 1);
                if (ws >= NS) ws -= NS;
                asm volatile(
                    "{\n.reg .pred p;\nelect.sync _|p, 0xffffffff;\n"
                    "@p mbarrier.arrive.expect_tx.shared::cta.b64 _, [%2], 7168;\n"
                    "@p cp.async.bulk.tensor.3d.shared::cluster.global.mbarrier::complete_tx::bytes.L2::cache_hint "
                    "[%0], [%1, {%3, %4, %3}], [%2], %5;\n}"
                    ::"r"(sbase + L::RING + ws * STAGE_BYTES + (k & 1) * SEG_BYTES), "l"(&p.wom[0]), "r"(bar_wo + k * 8),
                      "r"(0), "r"(k * 512 + slice * 8), "l"(pol) : "memory");
            }
        }
    } else if (warp == W + 1) {
        uint32_t tag;
        asm volatile("ld.relaxed.gpu.global.u32 %0, [%1];" : "=r"(tag) : "l"(&g_epoch) : "memory");
        tag += 1;
        auto wait_progress = [&](int target) {
            unsigned n = 0;
            while (s_tk[30] < target) {
                __nanosleep(100);
                if (++n > SPIN_LIMIT) __trap();
            }
        };
        {
            bool synced = false;
#pragma unroll 1
            for (int h = 0; h < 16; h++) {
                if (h == 1) wait_progress(Q_DELAY);
                unsigned n = 0;
                uint32_t qa[4], qb[4];
                while (true) {
                    bool ok = true;
#pragma unroll
                    for (int i = 0; i < 4; i++) ok &= ll_load(g_q + h * 128 + i * 32 + lane, qa[i], qb[i], tag);
                    if (!synced) {
                        asm volatile("bar.sync 2, %0;" ::"n"(NTHREADS) : "memory");
                        if (has_task) mbar_wait(bar_wqdone, 0);
                        synced = true;
                    }
                    if (__all_sync(0xffffffffu, ok)) break;
                    if (++n > SPIN_LIMIT) __trap();
                }
#pragma unroll
                for (int i = 0; i < 4; i++) s_q0[h * 128 + i * 32 + lane] = make_uint2(qa[i], qb[i]);
                __syncwarp();
                if (lane == 0) {
                    if (h == 0) mbar_arrive(bar_q);
                    if (h == 3) mbar_arrive(bar_q2);
                    if (h == 15) mbar_arrive(bar_q3);
                }
            }
        }
        if (has_task) {
            const uint32_t bit = tag & 1u, bitmask = 0u - bit;
            const int qh = slice >> 5;
            const int g = lane >> 2, t4 = lane & 3;
            pol = evict_first_policy();
            float y[7][4];
#pragma unroll
            for (int j = 0; j < 7; j++) { y[j][0] = 0.f; y[j][1] = 0.f; y[j][2] = 0.f; y[j][3] = 0.f; }
            const int h0 = isX ? 8 : 0;
#pragma unroll 1
            for (int h = h0; h < h0 + 8; h++) {
                {
                    uint32_t wf[14][4];
                    if (isX) {
                        wait_progress(h * 4096);
                        if (lane == 0) {
                            asm volatile("fence.proxy.async.shared::cta;" ::: "memory");
                            mbar_expect_tx(bar_wo + (h & 7) * 8, SEG_BYTES);
                            tma3d(sbase + L::SEG, &p.wom[1], (h & 7) * 512 + slice * 8, bar_wo + (h & 7) * 8, pol);
                        }
                        mbar_wait(bar_wo + (h & 7) * 8, 0);
                        load_wo_frags(wf, sbase + L::SEG, lane);
                        __syncwarp();
                    }
                    wait_progress(h < 15 ? (h + 1) * 4096 + MERGE_DELAY : PROG_END);
                    u64 ml[5];
                    uint4 ov[9];
                    const ulonglong2* pml = g_pml + ((h * G + lane) * 2 + qh) * 2;
                    const uint4* pr = g_po + ((size_t)(h * 32 + (slice >> 1)) * G + (lane >> 1)) * 4 + (slice & 1) * 2 + (lane & 1);
                    constexpr int PRS = 16 * 4;
                    const ulonglong2* pml4 = pml + (lane < G - 128 ? 4 * 128 : 0);
                    const uint4* pr8 = pr + (lane < (G - 128) * 2 ? 8 * PRS : 0);
#pragma unroll
                    for (int j = 0; j < 5; j++) ldu64(ml[j], j < 4 ? pml + j * 128 : pml4);
#pragma unroll
                    for (int it = 0; it < 9; it++) ld128(ov[it], it < 8 ? pr + it * PRS : pr8);
                    unsigned n = 0;
                    while (true) {
                        const uint32_t bad = or3(
                            or3(xor_or((uint32_t)(ml[0] >> 32), (uint32_t)(ml[1] >> 32), bitmask),
                                xor_or((uint32_t)(ml[2] >> 32), (uint32_t)(ml[3] >> 32), bitmask),
                                xor_or((uint32_t)(ml[4] >> 32), ov[0].x, bitmask)),
                            or3(xor_or(ov[1].x, ov[2].x, bitmask), xor_or(ov[3].x, ov[4].x, bitmask), xor_or(ov[5].x, ov[6].x, bitmask)),
                            xor_or(ov[7].x, ov[8].x, bitmask));
                        if (__all_sync(0xffffffffu, (bad & 1u) == 0) && (h == 15 || n > 0)) break;
                        if (h != 15) __nanosleep(400);
                        if (++n > SPIN_LIMIT) __trap();
#pragma unroll
                        for (int j = 0; j < 5; j++) ldu64_stale(ml[j], j < 4 ? pml + j * 128 : pml4, bit);
#pragma unroll
                        for (int it = 0; it < 9; it++) ld128_stale(ov[it], it < 8 ? pr + it * PRS : pr8, bit);
                    }
                    float mj[5];
#pragma unroll
                    for (int j = 0; j < 5; j++) mj[j] = __uint_as_float((uint32_t)ml[j]);
                    const float M = warp_max(fmaxf(fmaxf(fmaxf(mj[0], mj[1]), fmaxf(mj[2], mj[3])), mj[4]));
                    float wc[5], Ls = 0.f;
#pragma unroll
                    for (int j = 0; j < 5; j++) {
                        wc[j] = ex2(mj[j] - M);
                        if (j == 4 && lane >= G - 128) wc[j] = 0.f;
                        Ls += wc[j] * __uint_as_float((uint32_t)(ml[j] >> 32));
                    }
                    float a0 = 0.f, a1 = 0.f, a2 = 0.f, a3 = 0.f;
#pragma unroll
                    for (int it = 0; it < 9; it++) {
                        const float wv = __shfl_sync(0xffffffffu, wc[it >> 1], 16 * (it & 1) + (lane >> 1));
                        a0 += wv * __uint_as_float(ov[it].x);
                        a1 += wv * __uint_as_float(ov[it].y);
                        a2 += wv * __uint_as_float(ov[it].z);
                        a3 += wv * __uint_as_float(ov[it].w);
                        if (it == 0) Ls += __shfl_xor_sync(0xffffffffu, Ls, 1);
                    }
                    const bool up = lane & 2;
                    float ax = (up ? a2 : a0) + __shfl_xor_sync(0xffffffffu, up ? a0 : a2, 2);
                    float ay = (up ? a3 : a1) + __shfl_xor_sync(0xffffffffu, up ? a1 : a3, 2);
                    Ls += __shfl_xor_sync(0xffffffffu, Ls, 2);
#pragma unroll
                    for (int o = 4; o <= 16; o <<= 1) {
                        ax += __shfl_xor_sync(0xffffffffu, ax, o);
                        ay += __shfl_xor_sync(0xffffffffu, ay, o);
                        Ls += __shfl_xor_sync(0xffffffffu, Ls, o);
                    }
                    float inv;
                    asm("rcp.approx.ftz.f32 %0, %1;" : "=f"(inv) : "f"(Ls));
                    const uint32_t o2 = pack_bf16(ax * inv, ay * inv);
                    if (isY) {
                        if (lane < 4) s_ofin[h * 4 + lane] = o2;
                        __syncwarp();
                        if (h == 7 && lane == 0) mbar_arrive(bar_ofin);
                    } else {
                        project(y, wf, o2, lane);
                    }
                }
                if (h >= 14) {
                    const uint32_t obit = (h == 15) ? bit : bit ^ 1u;
                    char* dst = reinterpret_cast<char*>(g_ol + ((size_t)(56 + g) * 64 + slice) * 2) + t4 * 8;
#pragma unroll
                    for (int j = 0; j < 7; j++) st64(dst + (size_t)j * 8 * 64 * 32, pt_enc(y[j][0], obit), __float_as_uint(y[j][2]));
                }
            }
            if (cta == 127 && lane == 0) {
                asm volatile("st.relaxed.gpu.global.u32 [%0], %1;" ::"l"(&g_ticket), "r"(0u) : "memory");
                asm volatile("st.relaxed.gpu.global.u32 [%0], %1;" ::"l"(&g_epoch), "r"(tag) : "memory");
            }
        }
    } else {
        uint32_t tag;
        asm volatile("ld.relaxed.gpu.global.u32 %0, [%1];" : "=r"(tag) : "l"(&g_epoch) : "memory");
        const int g = lane >> 2, t4 = lane & 3;
        if (has_task) {
            const int tb = cta >> 6, qs = cta & 63;
            const int r = threadIdx.x >> 3, c8 = threadIdx.x & 7;
            const uint2* xp = reinterpret_cast<const uint2*>(p.x[tb] + 28 * r);
            uint2 xv[7];
#pragma unroll
            for (int i = 0; i < 7; i++)
                asm volatile("ld.global.nc.v2.u32 {%0,%1}, [%2];" : "=r"(xv[i].x), "=r"(xv[i].y) : "l"(xp + i));
            asm volatile("bar.sync 2, %0;" ::"n"(NTHREADS) : "memory");
            mbar_wait(bar_wq, 0);
            const uint4* wv = reinterpret_cast<const uint4*>(smem + L::RING + (NS - 4) * STAGE_BYTES) + 28 * r * 8 + c8;
            float acc[8];
#pragma unroll
            for (int j = 0; j < 8; j++) acc[j] = 0.f;
#pragma unroll
            for (int i = 0; i < 28; i++) {
                const uint32_t xw = (i & 2) ? xv[i >> 2].y : xv[i >> 2].x;
                const float xs = (i & 1) ? bf_hi(xw) : bf_lo(xw);
                const uint4 v = wv[i * 8];
                acc[0] += xs * bf_lo(v.x); acc[1] += xs * bf_hi(v.x);
                acc[2] += xs * bf_lo(v.y); acc[3] += xs * bf_hi(v.y);
                acc[4] += xs * bf_lo(v.z); acc[5] += xs * bf_hi(v.z);
                acc[6] += xs * bf_lo(v.w); acc[7] += xs * bf_hi(v.w);
            }
#pragma unroll
            for (int j = 0; j < 8; j++) {
                acc[j] += __shfl_xor_sync(0xffffffffu, acc[j], 8);
                acc[j] += __shfl_xor_sync(0xffffffffu, acc[j], 16);
            }
            if (lane < 8) {
                float4* d = reinterpret_cast<float4*>(s_red + warp * 64 + lane * 8);
                d[0] = make_float4(acc[0], acc[1], acc[2], acc[3]);
                d[1] = make_float4(acc[4], acc[5], acc[6], acc[7]);
            }
            asm volatile("bar.sync 1, %0;" ::"n"(W * 32) : "memory");
            if (threadIdx.x < 16) {
                const int il = threadIdx.x >> 2;
                float q[4];
#pragma unroll
                for (int k = 0; k < 4; k++) {
                    const int d = 16 * il + 2 * t4 + (k & 1) + 8 * (k >> 1);
                    q[k] = 0.f;
#pragma unroll
                    for (int w = 0; w < W; w++) q[k] += s_red[w * 64 + d];
                }
                ll_store(g_q + ((tb * 16 + (qs >> 2)) * 16 + (qs & 3) * 4 + il) * 4 + t4,
                         pack_bf16(q[0], q[1]), pack_bf16(q[2], q[3]), tag + 1);
            }
            __syncwarp();
            if (lane == 0) mbar_arrive(bar_wqdone);
        } else {
            asm volatile("bar.sync 2, %0;" ::"n"(NTHREADS) : "memory");
        }
        tag += 1;
        const uint32_t bit = tag & 1u;

        float acc[4][4];
#pragma unroll
        for (int i = 0; i < 4; i++) { acc[i][0] = 0.f; acc[i][1] = 0.f; acc[i][2] = 0.f; acc[i][3] = 0.f; }
        float m0 = -INFINITY, m1 = -INFINITY;
        float lacc[4] = {0.f, 0.f, 0.f, 0.f};
        const uint32_t ones[4] = {0x3f803f80u, 0x3f803f80u, 0x3f803f80u, 0x3f803f80u};
        uint32_t qf[16][2];
        int cur = 0;
        const uint32_t krow = (lane & 7) + 8 * ((lane >> 3) & 1), vrow = (lane & 7) + 8 * (lane >> 4);
        const uint32_t koff = krow * 128 + (((lane >> 4) ^ (krow & 7)) << 4);
        const uint32_t voff = TILE_BYTES + vrow * 128 + ((((lane >> 3) & 1) ^ (vrow & 7)) << 4);
        const float SC = 0.0625f * 1.4426950408889634f;
        char* const ydst = reinterpret_cast<char*>(g_ol + ((size_t)(8 * warp + g) * 64 + slice) * 2) + t4 * 8;
        int s = warp;
        uint32_t ph = 0;
        mbar_wait(bar_q, 0);
#pragma unroll
        for (int i = 0; i < 16; i++) {
            const uint2 v = s_q0[((g & 1) * 16 + i) * 4 + t4];
            qf[i][0] = v.x;
            qf[i][1] = v.y;
        }
        while (true) {
            mbar_wait(bar_full + s * 8, ph);
            const int t = s_tk[s];
            const int h = t >> 12;
            if (h != cur) {
                while (cur < h) {
                    float* sl = s_slots + warp * 2 * SLOT_STRIDE + 16 * t4 + 8 * (t4 >> 1) + g;
                    if (lane == 0) *reinterpret_cast<float4*>(s_slotml + warp * 4) = make_float4(m0, lacc[0], m1, lacc[1]);
#pragma unroll
                    for (int j = 0; j < 4; j++) {
                        sl[80 * j] = acc[j][0];
                        sl[80 * j + SLOT_STRIDE] = acc[j][1];
                        sl[80 * j + 8] = acc[j][2];
                        sl[80 * j + 8 + SLOT_STRIDE] = acc[j][3];
                    }
                    uint4* po = g_po + ((size_t)(cur * 32 + 8 * warp + (lane >> 2)) * G + cta) * 4 + (lane & 3);
                    ulonglong2* pml = g_pml + ((cur * G + cta) * 2 + (warp >> 1)) * 2 + lane;
                    asm volatile("bar.sync 1, %0;" ::"n"(W * 32) : "memory");
                    float2 mlw[W];
                    float4 sv[W];
                    float M = -INFINITY;
#pragma unroll
                    for (int w = 0; w < W; w++) {
                        mlw[w] = *reinterpret_cast<const float2*>(s_slotml + w * 4 + (warp & 2));
                        sv[w] = *reinterpret_cast<const float4*>(s_slots + (w * 2 + (warp >> 1)) * SLOT_STRIDE + 160 * (warp & 1) + 4 * lane + (lane & 24));
                        M = fmaxf(M, mlw[w].x);
                    }
                    const float R = (M == -INFINITY) ? 0.f : M;
                    float4 o = make_float4(0.f, 0.f, 0.f, 0.f);
                    float Lw = 0.f;
#pragma unroll
                    for (int w = 0; w < W; w++) {
                        const float f = ex2(mlw[w].x - R);
                        Lw += f * mlw[w].y;
                        o.x += f * sv[w].x; o.y += f * sv[w].y; o.z += f * sv[w].z; o.w += f * sv[w].w;
                    }
                    st128(po, pt_enc(o.x, bit), __float_as_uint(o.y), __float_as_uint(o.z), __float_as_uint(o.w));
                    const bool mlwriter = !(warp & 1) && lane < 2;
                    if (mlwriter) ll_store(pml, __float_as_uint(M), __float_as_uint(M), pt_enc(Lw, bit));
                    if (cur == 13) {
                        st128(po + 2 * 32 * G * 4, bit ^ 1u, 0u, 0u, 0u);
                        if (mlwriter) ll_store(pml + 2 * G * 4, 0u, 0u, bit ^ 1u);
                        if (isY) {
                            st64(ydst, bit ^ 1u, 0u);
                            if (warp < 3) st64(ydst + 4 * 8 * 64 * 32, bit ^ 1u, 0u);
                        }
                    }
#pragma unroll
                    for (int i = 0; i < 4; i++) { acc[i][0] = 0.f; acc[i][1] = 0.f; acc[i][2] = 0.f; acc[i][3] = 0.f; }
                    m0 = -INFINITY; m1 = -INFINITY;
                    lacc[0] = 0.f; lacc[1] = 0.f; lacc[2] = 0.f; lacc[3] = 0.f;
                    cur++;
                    asm volatile("bar.sync 1, %0;" ::"n"(W * 32) : "memory");
                }
                if (h >= 16) break;
                mbar_wait(h > 3 ? bar_q3 : bar_q2, 0);
#pragma unroll
                for (int i = 0; i < 16; i++) {
                    const uint2 v = s_q0[h * 128 + ((g & 1) * 16 + i) * 4 + t4];
                    qf[i][0] = v.x;
                    qf[i][1] = v.y;
                }
            }
            const uint32_t stage = sbase + L::RING + s * STAGE_BYTES;
            float sc[4][4];
#pragma unroll
            for (int c = 0; c < 4; c++) { sc[c][0] = 0.f; sc[c][1] = 0.f; sc[c][2] = 0.f; sc[c][3] = 0.f; }
            const uint32_t kb = stage + koff;
#pragma unroll
            for (int i = 0; i < 16; i++) {
                uint32_t a[4];
                ldsm4(a, (kb ^ ((i & 3) << 5)) + (i >> 2) * 2048);
                mma16816(sc[i & 3], a, qf[i][0], qf[i][1]);
            }
            const float s0 = ((sc[0][0] + sc[1][0]) + (sc[2][0] + sc[3][0])) * SC;
            const float s1 = ((sc[0][1] + sc[1][1]) + (sc[2][1] + sc[3][1])) * SC;
            const float s2 = ((sc[0][2] + sc[1][2]) + (sc[2][2] + sc[3][2])) * SC;
            const float s3 = ((sc[0][3] + sc[1][3]) + (sc[2][3] + sc[3][3])) * SC;
            float n0 = fmaxf(s0, s2), n1 = fmaxf(s1, s3);
            if (__any_sync(0xffffffffu, (n0 > m0) | (n1 > m1))) {
                n0 = fmaxf(warp_max(n0), m0);
                n1 = fmaxf(warp_max(n1), m1);
                const float f0 = ex2(m0 - n0), f1 = ex2(m1 - n1);
                m0 = n0; m1 = n1;
                lacc[0] *= f0; lacc[1] *= f1; lacc[2] *= f0; lacc[3] *= f1;
#pragma unroll
                for (int i = 0; i < 4; i++) { acc[i][0] *= f0; acc[i][1] *= f1; acc[i][2] *= f0; acc[i][3] *= f1; }
            }
            const float p0 = ex2(s0 - m0), p1 = ex2(s1 - m1), p2 = ex2(s2 - m0), p3 = ex2(s3 - m1);
            const uint32_t b0 = movtrans(pack_bf16(p0, p1));
            const uint32_t b1 = movtrans(pack_bf16(p2, p3));
            mma16816(lacc, ones, b0, b1);
            mbar_wait(bar_fullv + s * 8, ph);
            const uint32_t vb = stage + voff;
#pragma unroll
            for (int q = 0; q < 4; q++) {
                const uint32_t c0 = ((g >> 1) == q) ? b0 : 0u, c1 = ((g >> 1) == q) ? b1 : 0u;
#pragma unroll
                for (int j = 0; j < 4; j++) {
                    uint32_t a[4];
                    ldsm4t(a, (vb ^ (q << 5)) + j * 2048);
                    mma16816(acc[j], a, c0, c1);
                }
            }
            __syncwarp();
            if (lane == 0) mbar_arrive(bar_empty + s * 8);
            s += W;
            if (s >= NS) { s -= NS; ph ^= 1; }
        }

        if (isY) {
            mbar_wait(bar_ofin, 0);
            float y[7][4];
#pragma unroll
            for (int j = 0; j < 7; j++) { y[j][0] = 0.f; y[j][1] = 0.f; y[j][2] = 0.f; y[j][3] = 0.f; }
            float2* red = reinterpret_cast<float2*>(s_red);
#pragma unroll 1
            for (int k = warp; k < 8; k += W) {
                const uint32_t o2 = s_ofin[k * 4 + t4];
                int ws = s_tk[31] + (k >> 1);
                if (ws >= NS) ws -= NS;
                mbar_wait(bar_wo + k * 8, 0);
                uint32_t wf[14][4];
                load_wo_frags(wf, sbase + L::RING + ws * STAGE_BYTES + (k & 1) * SEG_BYTES, lane);
                project(y, wf, o2, lane);
            }
#pragma unroll
            for (int j = 0; j < 7; j++) red[(warp * 7 + j) * 32 + lane] = make_float2(y[j][0], y[j][2]);
            asm volatile("bar.sync 1, %0;" ::"n"(W * 32) : "memory");
#pragma unroll
            for (int jj = 0; jj < 2; jj++) {
                const int j = warp + 4 * jj;
                if (j < 7) {
                    float vx = 0.f, vy = 0.f;
#pragma unroll
                    for (int w = 0; w < W; w++) {
                        const float2 v = red[(w * 7 + j) * 32 + lane];
                        vx += v.x;
                        vy += v.y;
                    }
                    st64(ydst + jj * 4 * 8 * 64 * 32, pt_enc(vx, bit), __float_as_uint(vy));
                }
            }
        }
        if (isX && slice < 56 && !(warp & 1)) {
            const bool fb = warp < 2;
            const uint32_t bitmask = 0u - bit;
            const uint4* src = g_ol + (size_t)((fb ? 56 : 0) + slice) * 64 * 2 + lane;
            const int et = 2 * (lane & 1) + ((lane >> 1) & 1), es = (lane >> 2) & 1;
            const int col = (fb ? DM : 0) + 64 * (slice >> 3) + 16 * et + 8 * es + (slice & 7);
            __nv_bfloat16* dst = p.out + col;
            unsigned n = 0;
            while (true) {
                uint4 v[4];
#pragma unroll
                for (int i = 0; i < 4; i++) ld2x64(v[i], src + i * 32);
                const uint32_t bad = or3(xor_or(v[0].x, v[0].z, bitmask), xor_or(v[1].x, v[1].z, bitmask),
                                         xor_or(v[2].x, v[2].z, bitmask)) | xor_or(v[3].x, v[3].z, bitmask);
                const bool done = __all_sync(0xffffffffu, (bad & 1u) == 0);
                const float a0 = (__uint_as_float(v[0].x) + __uint_as_float(v[1].x)) + (__uint_as_float(v[2].x) + __uint_as_float(v[3].x));
                const float a1 = (__uint_as_float(v[0].y) + __uint_as_float(v[1].y)) + (__uint_as_float(v[2].y) + __uint_as_float(v[3].y));
                const float a2 = (__uint_as_float(v[0].z) + __uint_as_float(v[1].z)) + (__uint_as_float(v[2].z) + __uint_as_float(v[3].z));
                const float a3 = (__uint_as_float(v[0].w) + __uint_as_float(v[1].w)) + (__uint_as_float(v[2].w) + __uint_as_float(v[3].w));
                if (done || n == 0) {
                    const bool u1 = lane & 2, u2 = lane & 4;
                    const float bx = (u1 ? a2 : a0) + __shfl_xor_sync(0xffffffffu, u1 ? a0 : a2, 2);
                    const float by = (u1 ? a3 : a1) + __shfl_xor_sync(0xffffffffu, u1 ? a1 : a3, 2);
                    float c = (u2 ? by : bx) + __shfl_xor_sync(0xffffffffu, u2 ? bx : by, 4);
                    c += __shfl_xor_sync(0xffffffffu, c, 8);
                    c += __shfl_xor_sync(0xffffffffu, c, 16);
                    if (done && lane < 8) *dst = __float2bfloat16(c);
                    if (done) break;
                }
                if (++n > SPIN_LIMIT) __trap();
            }
        }
    }
}

constexpr int FB_SPLIT = 64;
__device__ float g_fq[2 * 4096];
__device__ float g_fp[16 * FB_SPLIT * 8 * 2 * 264];

__global__ void fb_q_kernel(const __nv_bfloat16* x, const __nv_bfloat16* wq, int b) {
    const int n = blockIdx.x * blockDim.x + threadIdx.x;
    float a = 0.f;
    for (int k = 0; k < DM; k++) a += __bfloat162float(x[k]) * __bfloat162float(wq[(size_t)k * 4096 + n]);
    g_fq[b * 4096 + n] = __bfloat162float(__float2bfloat16(a));
}
__global__ void fb_attn_kernel(const uint4* k, const uint4* v, int b) {
    const int hk = blockIdx.y, warp = threadIdx.x >> 5, lane = threadIdx.x & 31;
    float q[2][8], o[2][8], m[2] = {-INFINITY, -INFINITY}, l[2] = {0.f, 0.f};
    for (int h = 0; h < 2; h++)
        for (int j = 0; j < 8; j++) { q[h][j] = g_fq[b * 4096 + (hk * 2 + h) * 256 + lane * 8 + j]; o[h][j] = 0.f; }
    const int n = 65536 / FB_SPLIT / 8;
    const size_t row0 = (size_t)hk * 65536 + (size_t)(blockIdx.x * 8 + warp) * n;
    for (int i = 0; i < n; i++) {
        const uint4 kk = k[(row0 + i) * 32 + lane], vv = v[(row0 + i) * 32 + lane];
        const float kf[8] = {bf_lo(kk.x), bf_hi(kk.x), bf_lo(kk.y), bf_hi(kk.y), bf_lo(kk.z), bf_hi(kk.z), bf_lo(kk.w), bf_hi(kk.w)};
        const float vf[8] = {bf_lo(vv.x), bf_hi(vv.x), bf_lo(vv.y), bf_hi(vv.y), bf_lo(vv.z), bf_hi(vv.z), bf_lo(vv.w), bf_hi(vv.w)};
#pragma unroll
        for (int h = 0; h < 2; h++) {
            float s = 0.f;
#pragma unroll
            for (int j = 0; j < 8; j++) s += q[h][j] * kf[j];
            for (int d = 16; d >= 1; d >>= 1) s += __shfl_xor_sync(0xffffffffu, s, d);
            s *= 0.0625f * 1.4426950408889634f;
            const float mn = fmaxf(m[h], s), f = ex2(m[h] - mn), pr = ex2(s - mn);
            m[h] = mn;
            l[h] = l[h] * f + pr;
#pragma unroll
            for (int j = 0; j < 8; j++) o[h][j] = o[h][j] * f + pr * vf[j];
        }
    }
    for (int h = 0; h < 2; h++) {
        float* d = g_fp + ((((size_t)(b * 8 + hk) * FB_SPLIT + blockIdx.x) * 8 + warp) * 2 + h) * 264;
        for (int j = 0; j < 8; j++) d[lane * 8 + j] = o[h][j];
        if (lane == 0) { d[256] = m[h]; d[257] = l[h]; }
    }
}
__global__ void fb_merge_kernel() {
    const int hq = blockIdx.x;
    const float* base = g_fp + ((size_t)(hq >> 1) * FB_SPLIT * 8 * 2 + (hq & 1)) * 264;
    float M = -INFINITY, Ls = 0.f, a = 0.f;
    for (int i = 0; i < FB_SPLIT * 8; i++) M = fmaxf(M, base[(size_t)i * 528 + 256]);
    for (int i = 0; i < FB_SPLIT * 8; i++) {
        const float w = ex2(base[(size_t)i * 528 + 256] - M);
        Ls += w * base[(size_t)i * 528 + 257];
        a += w * base[(size_t)i * 528 + threadIdx.x];
    }
    g_fq[hq * 256 + threadIdx.x] = __bfloat162float(__float2bfloat16(a / Ls));
}
__global__ void fb_out_kernel(const __nv_bfloat16* wo, __nv_bfloat16* out, int b) {
    const int n = blockIdx.x * 64 + threadIdx.x;
    float a = 0.f;
    for (int k = 0; k < 4096; k++) a += g_fq[b * 4096 + k] * __bfloat162float(wo[(size_t)k * DM + n]);
    out[b * DM + n] = __float2bfloat16(a);
}

typedef CUresult (*EncodeFn)(CUtensorMap*, CUtensorMapDataType, cuuint32_t, void*, const cuuint64_t*, const cuuint64_t*,
                             const cuuint32_t*, const cuuint32_t*, CUtensorMapInterleave, CUtensorMapSwizzle,
                             CUtensorMapL2promotion, CUtensorMapFloatOOBfill);

void encode_kv(EncodeFn enc, CUtensorMap* m, const void* ptr) {
    cuuint64_t gd[3] = {64, 8ull * 65536ull, 4};
    cuuint64_t gs[2] = {512, 128};
    cuuint32_t box[3] = {64, 16, 4};
    cuuint32_t es[3] = {1, 1, 1};
    enc(m, CU_TENSOR_MAP_DATA_TYPE_BFLOAT16, 3, const_cast<void*>(ptr), gd, gs, box, es, CU_TENSOR_MAP_INTERLEAVE_NONE,
        CU_TENSOR_MAP_SWIZZLE_128B, CU_TENSOR_MAP_L2_PROMOTION_L2_256B, CU_TENSOR_MAP_FLOAT_OOB_FILL_NONE);
}

void encode_wo(EncodeFn enc, CUtensorMap* m, const void* ptr) {
    cuuint64_t gd[3] = {64, 4096, 7};
    cuuint64_t gs[2] = {DM * 2, 128};
    cuuint32_t box[3] = {64, 8, 7};
    cuuint32_t es[3] = {1, 1, 1};
    enc(m, CU_TENSOR_MAP_DATA_TYPE_BFLOAT16, 3, const_cast<void*>(ptr), gd, gs, box, es, CU_TENSOR_MAP_INTERLEAVE_NONE,
        CU_TENSOR_MAP_SWIZZLE_128B, CU_TENSOR_MAP_L2_PROMOTION_L2_128B, CU_TENSOR_MAP_FLOAT_OOB_FILL_NONE);
}

void encode_wq(EncodeFn enc, CUtensorMap* m, const void* ptr) {
    cuuint64_t gd[2] = {4096, 448};
    cuuint64_t gs[1] = {8192};
    cuuint32_t box[2] = {64, 224};
    cuuint32_t es[2] = {1, 1};
    enc(m, CU_TENSOR_MAP_DATA_TYPE_BFLOAT16, 2, const_cast<void*>(ptr), gd, gs, box, es, CU_TENSOR_MAP_INTERLEAVE_NONE,
        CU_TENSOR_MAP_SWIZZLE_NONE, CU_TENSOR_MAP_L2_PROMOTION_L2_128B, CU_TENSOR_MAP_FLOAT_OOB_FILL_NONE);
}

}

extern "C" void kernel_launch(void* const* d_in, const int* in_sizes, int n_in, void* d_out, int out_size) {
    (void)in_sizes; (void)n_in; (void)out_size;
    static EncodeFn enc = nullptr;
    static int mode = -1;
    if (mode < 0) {
        cudaDriverEntryPointQueryResult qr;
        void* fn = nullptr;
        cudaGetDriverEntryPoint("cuTensorMapEncodeTiled", &fn, cudaEnableDefault, &qr);
        enc = (EncodeFn)fn;
        int dev = 0, sms = 0, occ = 0;
        cudaGetDevice(&dev);
        cudaDeviceGetAttribute(&sms, cudaDevAttrMultiProcessorCount, dev);
        const bool attr_ok =
            cudaFuncSetAttribute(fused_decode_kernel, cudaFuncAttributeMaxDynamicSharedMemorySize, L::SIZE) == cudaSuccess;
        if (attr_ok) cudaOccupancyMaxActiveBlocksPerMultiprocessor(&occ, fused_decode_kernel, NTHREADS, L::SIZE);
        mode = (enc != nullptr && attr_ok && sms * occ >= G) ? 1 : 0;
        (void)cudaGetLastError();
    }
    if (mode == 1) {
        Params p;
        for (int b = 0; b < 2; b++) {
            p.x[b] = (const __nv_bfloat16*)d_in[5 * b + 0];
            encode_kv(enc, &p.km[b], d_in[5 * b + 1]);
            encode_kv(enc, &p.vm[b], d_in[5 * b + 2]);
            encode_wq(enc, &p.wqm[b], d_in[5 * b + 3]);
            encode_wo(enc, &p.wom[b], d_in[5 * b + 4]);
        }
        p.out = (__nv_bfloat16*)d_out;
        fused_decode_kernel<<<G, NTHREADS, L::SIZE>>>(p);
    } else {
        for (int b = 0; b < 2; b++) {
            fb_q_kernel<<<16, 256>>>((const __nv_bfloat16*)d_in[5 * b], (const __nv_bfloat16*)d_in[5 * b + 3], b);
            fb_attn_kernel<<<dim3(FB_SPLIT, 8), 256>>>((const uint4*)d_in[5 * b + 1], (const uint4*)d_in[5 * b + 2], b);
        }
        fb_merge_kernel<<<32, 256>>>();
        for (int b = 0; b < 2; b++)
            fb_out_kernel<<<7, 64>>>((const __nv_bfloat16*)d_in[5 * b + 4], (__nv_bfloat16*)d_out, b);
    }
}
```

```cpp
#include <cuda_runtime.h>
#include <cuda_bf16.h>
#include <cuda.h>
#include <stdint.h>

namespace {

constexpr int G = 132;
constexpr int W = 4;
constexpr int NTHREADS = (W + 2) * 32;
constexpr int TILE_BYTES = 8192;
constexpr int STAGE_BYTES = 2 * TILE_BYTES;
constexpr int TOTAL = 65536;
constexpr int DM = 448;
constexpr int SEG_BYTES = 8 * DM * 2;
constexpr int SLOT_STRIDE = 320;
constexpr int PROG_END = 1 << 30;
constexpr int NS = 12;
constexpr int K0 = 3;
constexpr int Q_DELAY = 1500;
constexpr int MERGE_DELAY = 2500;
constexpr int CAP = 4, CAP_END = 3;
constexpr int END_ZONE = 1000;
constexpr unsigned SPIN_LIMIT = 1u << 22;

struct Params {
    const __nv_bfloat16* x[2];
    __nv_bfloat16* out;
    CUtensorMap km[2];
    CUtensorMap vm[2];
    CUtensorMap wqm[2];
    CUtensorMap wom[2];
};

typedef unsigned long long u64;

__device__ unsigned int g_epoch;
__device__ unsigned int g_ticket;
__device__ ulonglong2 g_q[16 * 2 * 16 * 4];
__device__ uint4 g_po[16 * 32 * G * 4];
__device__ ulonglong2 g_pml[16 * G * 2 * 2];
__device__ uint4 g_ol[2 * 56 * 64 * 2];

__device__ __forceinline__ uint32_t smem_u32(const void* p) { return (uint32_t)__cvta_generic_to_shared(p); }
__device__ __forceinline__ void mbar_init(uint32_t bar, uint32_t cnt) {
    asm volatile("mbarrier.init.shared::cta.b64 [%0], %1;" ::"r"(bar), "r"(cnt) : "memory");
}
__device__ __forceinline__ void mbar_expect_tx(uint32_t bar, uint32_t bytes) {
    asm volatile("mbarrier.arrive.expect_tx.shared::cta.b64 _, [%0], %1;" ::"r"(bar), "r"(bytes) : "memory");
}
__device__ __forceinline__ void mbar_arrive(uint32_t bar) {
    asm volatile("mbarrier.arrive.shared::cta.b64 _, [%0];" ::"r"(bar) : "memory");
}
__device__ __forceinline__ bool mbar_try(uint32_t bar, uint32_t parity) {
    uint32_t ok;
    asm volatile("{\n.reg .pred p;\nmbarrier.try_wait.parity.shared::cta.b64 p, [%1], %2;\nselp.u32 %0, 1, 0, p;\n}"
                 : "=r"(ok) : "r"(bar), "r"(parity) : "memory");
    return ok != 0;
}
__device__ __forceinline__ void mbar_wait(uint32_t bar, uint32_t parity) {
    unsigned n = 0;
    while (!mbar_try(bar, parity)) {
        if (++n > SPIN_LIMIT) __trap();
    }
}
__device__ __forceinline__ void tma3d(uint32_t dst, const CUtensorMap* m, int row, uint32_t bar, uint64_t pol) {
    asm volatile(
        "cp.async.bulk.tensor.3d.shared::cluster.global.mbarrier::complete_tx::bytes.L2::cache_hint "
        "[%0], [%1, {%3, %4, %3}], [%2], %5;" ::"r"(dst), "l"(m), "r"(bar), "r"(0), "r"(row), "l"(pol)
        : "memory");
}
__device__ __forceinline__ uint64_t evict_first_policy() {
    uint64_t pol;
    asm volatile("createpolicy.fractional.L2::evict_first.b64 %0, 1.0;" : "=l"(pol));
    return pol;
}
__device__ __forceinline__ void ldsm4(uint32_t (&r)[4], uint32_t addr) {
    asm volatile("ldmatrix.sync.aligned.m8n8.x4.shared.b16 {%0,%1,%2,%3}, [%4];"
                 : "=r"(r[0]), "=r"(r[1]), "=r"(r[2]), "=r"(r[3]) : "r"(addr) : "memory");
}
__device__ __forceinline__ void ldsm4t(uint32_t (&r)[4], uint32_t addr) {
    asm volatile("ldmatrix.sync.aligned.m8n8.x4.trans.shared.b16 {%0,%1,%2,%3}, [%4];"
                 : "=r"(r[0]), "=r"(r[1]), "=r"(r[2]), "=r"(r[3]) : "r"(addr) : "memory");
}
__device__ __forceinline__ void mma16816(float (&c)[4], const uint32_t (&a)[4], uint32_t b0, uint32_t b1) {
    asm volatile("mma.sync.aligned.m16n8k16.row.col.f32.bf16.bf16.f32 {%0,%1,%2,%3}, {%4,%5,%6,%7}, {%8,%9}, {%0,%1,%2,%3};"
                 : "+f"(c[0]), "+f"(c[1]), "+f"(c[2]), "+f"(c[3])
                 : "r"(a[0]), "r"(a[1]), "r"(a[2]), "r"(a[3]), "r"(b0), "r"(b1));
}
__device__ __forceinline__ uint32_t movtrans(uint32_t a) {
    uint32_t d;
    asm volatile("movmatrix.sync.aligned.m8n8.trans.b16 %0, %1;" : "=r"(d) : "r"(a));
    return d;
}
__device__ __forceinline__ float ex2(float x) {
    float y;
    asm("ex2.approx.ftz.f32 %0, %1;" : "=f"(y) : "f"(x));
    return y;
}
__device__ __forceinline__ uint32_t pack_bf16(float lo, float hi) {
    uint32_t d;
    asm("cvt.rn.bf16x2.f32 %0, %1, %2;" : "=r"(d) : "f"(hi), "f"(lo));
    return d;
}
__device__ __forceinline__ float bf_lo(uint32_t v) { return __uint_as_float(v << 16); }
__device__ __forceinline__ float bf_hi(uint32_t v) { return __uint_as_float(v & 0xffff0000u); }
__device__ __forceinline__ float warp_max(float v) {
    int k = __float_as_int(v);
    k ^= (k >> 31) & 0x7fffffff;
    k = __reduce_max_sync(0xffffffffu, k);
    k ^= (k >> 31) & 0x7fffffff;
    return __int_as_float(k);
}

__device__ __forceinline__ u64 ll_word(uint32_t v, uint32_t tag) { return ((u64)tag << 32) | v; }
__device__ __forceinline__ void ll_store(ulonglong2* p, uint32_t a, uint32_t b, uint32_t tag) {
    asm volatile("st.relaxed.gpu.global.v2.b64 [%0], {%1, %2};" ::"l"(p), "l"(ll_word(a, tag)), "l"(ll_word(b, tag)) : "memory");
}
__device__ __forceinline__ bool ll_ok(u64 x, u64 y, uint32_t tag) {
    return ((uint32_t)(x >> 32) == tag) & ((uint32_t)(y >> 32) == tag);
}
__device__ __forceinline__ uint32_t pt_enc(float v, uint32_t bit) { return (__float_as_uint(v) & ~1u) | bit; }
__device__ __forceinline__ uint32_t xor_or(uint32_t a, uint32_t b, uint32_t m) {
    uint32_t d;
    asm("lop3.b32 %0, %1, %2, %3, 0x7e;" : "=r"(d) : "r"(a), "r"(b), "r"(m));
    return d;
}
__device__ __forceinline__ uint32_t or3(uint32_t a, uint32_t b, uint32_t c) {
    uint32_t d;
    asm("lop3.b32 %0, %1, %2, %3, 0xfe;" : "=r"(d) : "r"(a), "r"(b), "r"(c));
    return d;
}
__device__ __forceinline__ void st128(uint4* p, uint32_t a, uint32_t b, uint32_t c, uint32_t d) {
    asm volatile("{\n.reg .b128 t;\n.reg .b64 lo, hi;\nmov.b64 lo, {%1, %2};\nmov.b64 hi, {%3, %4};\nmov.b128 t, {lo, hi};\n"
                 "st.relaxed.gpu.global.b128 [%0], t;\n}" ::"l"(p), "r"(a), "r"(b), "r"(c), "r"(d) : "memory");
}
__device__ __forceinline__ void ld128(uint4& v, const uint4* p) {
    asm volatile("{\n.reg .b128 t;\n.reg .b64 lo, hi;\nld.relaxed.gpu.global.b128 t, [%4];\nmov.b128 {lo, hi}, t;\n"
                 "mov.b64 {%0, %1}, lo;\nmov.b64 {%2, %3}, hi;\n}"
                 : "=r"(v.x), "=r"(v.y), "=r"(v.z), "=r"(v.w) : "l"(p) : "memory");
}
__device__ __forceinline__ void ld128_stale(uint4& v, const uint4* p, uint32_t bit) {
    asm volatile("{\n.reg .pred p;\n.reg .b32 u;\n.reg .b128 t;\n.reg .b64 lo, hi;\nand.b32 u, %0, 1;\nsetp.ne.u32 p, u, %5;\n"
                 "mov.b64 lo, {%0, %1};\nmov.b64 hi, {%2, %3};\nmov.b128 t, {lo, hi};\n"
                 "@p ld.relaxed.gpu.global.b128 t, [%4];\nmov.b128 {lo, hi}, t;\nmov.b64 {%0, %1}, lo;\nmov.b64 {%2, %3}, hi;\n}"
                 : "+r"(v.x), "+r"(v.y), "+r"(v.z), "+r"(v.w) : "l"(p), "r"(bit) : "memory");
}
__device__ __forceinline__ void st64(void* p, uint32_t a, uint32_t b) {
    asm volatile("{\n.reg .b64 t;\nmov.b64 t, {%1, %2};\nst.relaxed.gpu.global.b64 [%0], t;\n}" ::"l"(p), "r"(a), "r"(b) : "memory");
}
__device__ __forceinline__ void ld2x64(uint4& v, const uint4* p) {
    asm volatile("{\n.reg .b64 lo, hi;\nld.relaxed.gpu.global.v2.b64 {lo, hi}, [%4];\nmov.b64 {%0, %1}, lo;\nmov.b64 {%2, %3}, hi;\n}"
                 : "=r"(v.x), "=r"(v.y), "=r"(v.z), "=r"(v.w) : "l"(p) : "memory");
}
__device__ __forceinline__ void ldu64(u64& v, const void* p) {
    asm volatile("ld.relaxed.gpu.global.b64 %0, [%1];" : "=l"(v) : "l"(p) : "memory");
}
__device__ __forceinline__ void ldu64_stale(u64& v, const void* p, uint32_t bit) {
    asm volatile("{\n.reg .pred p;\n.reg .b32 a, b;\nmov.b64 {a, b}, %0;\nand.b32 b, b, 1;\nsetp.ne.u32 p, b, %2;\n"
                 "@p ld.relaxed.gpu.global.b64 %0, [%1];\n}" : "+l"(v) : "l"(p), "r"(bit) : "memory");
}
__device__ __forceinline__ void mma1688(float (&c)[4], uint32_t a0, uint32_t a1, uint32_t b0) {
    asm volatile("mma.sync.aligned.m16n8k8.row.col.f32.bf16.bf16.f32 {%0,%1,%2,%3}, {%4,%5}, {%6}, {%0,%1,%2,%3};"
                 : "+f"(c[0]), "+f"(c[1]), "+f"(c[2]), "+f"(c[3]) : "r"(a0), "r"(a1), "r"(b0));
}
__device__ __forceinline__ bool ll_load(const ulonglong2* p, uint32_t& a, uint32_t& b, uint32_t tag) {
    u64 x, y;
    asm volatile("ld.relaxed.gpu.global.v2.b64 {%0, %1}, [%2];" : "=l"(x), "=l"(y) : "l"(p) : "memory");
    a = (uint32_t)x;
    b = (uint32_t)y;
    return ll_ok(x, y, tag);
}

__device__ __forceinline__ void load_wo_frags(uint32_t (&wf)[14][4], uint32_t seg, int lane) {
    const uint32_t row = 4 * ((lane >> 1) & 1) + 2 * ((lane >> 2) & 1) + (lane & 1);
    const uint32_t a = seg + row * 128 + ((((uint32_t)lane >> 3) ^ row) << 4);
#pragma unroll
    for (int x = 0; x < 14; x++) ldsm4t(wf[x], (a ^ ((x & 1) << 6)) + (x >> 1) * 1024);
}
__device__ __forceinline__ void project(float (&y)[7][4], const uint32_t (&wf)[14][4], uint32_t o2, int lane) {
#pragma unroll
    for (int q = 0; q < 4; q++) {
        const uint32_t bq = ((lane >> 2) == 2 * q) ? o2 : 0u;
#pragma unroll
        for (int j = 0; j < 7; j++) {
            const int i = 4 * j + q;
            mma1688(y[j], wf[i >> 1][2 * (i & 1)], wf[i >> 1][2 * (i & 1) + 1], bq);
        }
    }
}

struct L {
    static constexpr int RING = 0;
    static constexpr int SEG = NS * STAGE_BYTES;
    static constexpr int SLOTS = SEG + SEG_BYTES;
    static constexpr int Q0 = SLOTS + W * 2 * SLOT_STRIDE * 4;
    static constexpr int SLOTML = Q0 + 16 * 128 * 8;
    static constexpr int OFIN = SLOTML + W * 16;
    static constexpr int TK = OFIN + 32 * 4;
    static constexpr int BARS = TK + 32 * 4;
    static constexpr int NBARS = 3 * NS + 6 + 8;
    static constexpr int SIZE = BARS + NBARS * 8;
};

__global__ void __launch_bounds__(NTHREADS, 1) fused_decode_kernel(const __grid_constant__ Params p) {
    extern __shared__ __align__(1024) unsigned char smem_raw[];
    static_assert(NS % W == 0 && K0 >= 2 && K0 <= NS - 4 && W == 4, "geometry");
    unsigned char* smem = smem_raw;
    const uint32_t sbase = smem_u32(smem);
    const int warp = threadIdx.x >> 5, lane = threadIdx.x & 31;
    const int cta = blockIdx.x;
    const bool has_task = cta < 128;
    const bool isX = has_task && cta >= 64, isY = cta < 64;
    const int slice = cta & 63;

    const uint32_t bar_full = sbase + L::BARS;
    const uint32_t bar_fullv = bar_full + NS * 8;
    const uint32_t bar_empty = bar_fullv + NS * 8;
    const uint32_t bar_wq = bar_empty + NS * 8;
    const uint32_t bar_q = bar_wq + 8;
    const uint32_t bar_q2 = bar_q + 8;
    const uint32_t bar_q3 = bar_q2 + 8;
    const uint32_t bar_ofin = bar_q3 + 8;
    const uint32_t bar_wo = bar_ofin + 8;
    const uint32_t bar_wqdone = bar_wo + 64;
    volatile int* s_tk = reinterpret_cast<volatile int*>(smem + L::TK);
    float* s_slots = reinterpret_cast<float*>(smem + L::SLOTS);
    float* s_slotml = reinterpret_cast<float*>(smem + L::SLOTML);
    float* s_red = reinterpret_cast<float*>(smem + L::SEG);
    uint32_t* s_ofin = reinterpret_cast<uint32_t*>(smem + L::OFIN);
    uint2* s_q0 = reinterpret_cast<uint2*>(smem + L::Q0);

    uint64_t pol = 0;
    auto issue = [&](int s, int t) {
        s_tk[s] = t;
        s_tk[30] = t;
        const uint32_t dst = sbase + L::RING + s * STAGE_BYTES;
        const int b = t >> 15, row = (t & 32767) << 4;
        mbar_expect_tx(bar_full + s * 8, TILE_BYTES);
        tma3d(dst, &p.km[b], row, bar_full + s * 8, pol);
        mbar_expect_tx(bar_fullv + s * 8, TILE_BYTES);
        tma3d(dst + TILE_BYTES, &p.vm[b], row, bar_fullv + s * 8, pol);
    };
    if (threadIdx.x == W * 32) {
        mbar_init(bar_wq, 1);
#pragma unroll
        for (int i = 0; i < K0; i++) { mbar_init(bar_full + i * 8, 1); mbar_init(bar_fullv + i * 8, 1); }
        asm volatile("fence.mbarrier_init.release.cluster;" ::: "memory");
        pol = evict_first_policy();
        if (has_task) {
            mbar_expect_tx(bar_wq, 448 * 128);
#pragma unroll
            for (int i = 0; i < 2; i++)
                asm volatile(
                    "cp.async.bulk.tensor.2d.shared::cluster.global.mbarrier::complete_tx::bytes.L2::cache_hint "
                    "[%0], [%1, {%3, %4}], [%2], %5;" ::"r"(sbase + L::RING + (NS - 4) * STAGE_BYTES + i * 224 * 128),
                    "l"(&p.wqm[cta >> 6]), "r"(bar_wq), "r"((cta & 63) * 64), "r"(i * 224), "l"(pol) : "memory");
        }
#pragma unroll
        for (int i = 0; i < K0; i++) issue(i, cta + G * i);
#pragma unroll
        for (int i = 0; i < L::NBARS; i++)
            if (!(i < K0 || (i >= NS && i < NS + K0) || i == 3 * NS)) mbar_init(bar_full + i * 8, i == L::NBARS - 1 ? W : 1);
        asm volatile("fence.mbarrier_init.release.cluster;" ::: "memory");
    }

    if (warp == W) {
        __syncwarp();
        asm volatile("bar.arrive 2, %0;" ::"n"(NTHREADS) : "memory");
        if (lane == 0) {
            asm volatile("prefetch.tensormap [%0];" ::"l"(&p.km[1]) : "memory");
            asm volatile("prefetch.tensormap [%0];" ::"l"(&p.vm[1]) : "memory");
            asm volatile("prefetch.tensormap [%0];" ::"l"(&p.wom[0]) : "memory");
        }
        pol = evict_first_policy();
        int s = K0, cnt = K0, t = 0;
        uint32_t ph = 1;
        bool first_lap = has_task;
        while (true) {
            const int cap = (t >= TOTAL - END_ZONE) ? CAP_END : CAP;
            if (cnt >= cap) {
                int sd = s - cap;
                uint32_t pd = ph ^ 1;
                if (sd < 0) { sd += NS; pd ^= 1; }
                mbar_wait((cap == CAP ? bar_full : bar_fullv) + sd * 8, pd);
            }
            cnt++;
            unsigned v = 0;
            if (lane == 0) asm volatile("atom.relaxed.gpu.global.inc.u32 %0, [%1], 0x7fffffff;" : "=r"(v) : "l"(&g_ticket) : "memory");
            mbar_wait(bar_empty + s * 8, ph);
            if (first_lap && s == NS - 4) { mbar_wait(bar_wqdone, 0); first_lap = false; }
            t = (int)__shfl_sync(0xffffffffu, v, 0) + G * K0;
            if (t >= TOTAL) break;
            const uint32_t dst = sbase + L::RING + s * STAGE_BYTES;
            const int b = t >> 15;
            asm volatile(
                "{\n.reg .pred p;\nelect.sync _|p, 0xffffffff;\n"
                "@p st.volatile.shared.u32 [%8], %9;\n"
                "@p st.volatile.shared.u32 [%10], %9;\n"
                "@p mbarrier.arrive.expect_tx.shared::cta.b64 _, [%3], 8192;\n"
                "@p cp.async.bulk.tensor.3d.shared::cluster.global.mbarrier::complete_tx::bytes.L2::cache_hint "
                "[%0], [%1, {%5, %6, %5}], [%3], %7;\n"
                "@p mbarrier.arrive.expect_tx.shared::cta.b64 _, [%4], 8192;\n"
                "@p cp.async.bulk.tensor.3d.shared::cluster.global.mbarrier::complete_tx::bytes.L2::cache_hint "
                "[%11], [%2, {%5, %6, %5}], [%4], %7;\n}"
                ::"r"(dst), "l"(&p.km[b]), "l"(&p.vm[b]), "r"(bar_full + s * 8), "r"(bar_fullv + s * 8), "r"(0),
                  "r"((t & 32767) << 4), "l"(pol), "r"(sbase + L::TK + s * 4), "r"(t), "r"(sbase + L::TK + 30 * 4),
                  "r"(dst + TILE_BYTES) : "memory");
            if (++s == NS) { s = 0; ph ^= 1; }
        }
        if (lane == 0) {
            s_tk[30] = PROG_END;
            s_tk[31] = s;
        }
        __syncwarp();
        if (lane < W) {
            int sj = s + lane;
            uint32_t pj = ph;
            if (sj >= NS) { sj -= NS; pj ^= 1; }
            mbar_wait(bar_empty + sj * 8, pj);
            s_tk[sj] = TOTAL;
            mbar_arrive(bar_full + sj * 8);
        }
        __syncwarp();
        if (isY) {
            mbar_wait(bar_wqdone, 0);
            {
                int sd = s - 2;
                uint32_t pd = ph ^ 1;
                if (sd < 0) { sd += NS; pd ^= 1; }
                mbar_wait(bar_full + sd * 8, pd);
            }
#pragma unroll
            for (int k = 0; k < 8; k++) {
                int ws = s + (k >> 1);
                if (ws >= NS) ws -= NS;
                asm volatile(
                    "{\n.reg .pred p;\nelect.sync _|p, 0xffffffff;\n"
                    "@p mbarrier.arrive.expect_tx.shared::cta.b64 _, [%2], 7168;\n"
                    "@p cp.async.bulk.tensor.3d.shared::cluster.global.mbarrier::complete_tx::bytes.L2::cache_hint "
                    "[%0], [%1, {%3, %4, %3}], [%2], %5;\n}"
                    ::"r"(sbase + L::RING + ws * STAGE_BYTES + (k & 1) * SEG_BYTES), "l"(&p.wom[0]), "r"(bar_wo + k * 8),
                      "r"(0), "r"(k * 512 + slice * 8), "l"(pol) : "memory");
            }
        }
    } else if (warp == W + 1) {
        uint32_t tag;
        asm volatile("ld.relaxed.gpu.global.u32 %0, [%1];" : "=r"(tag) : "l"(&g_epoch) : "memory");
        tag += 1;
        auto wait_progress = [&](int target) {
            unsigned n = 0;
            while (s_tk[30] < target) {
                __nanosleep(100);
                if (++n > SPIN_LIMIT) __trap();
            }
        };
        {
            bool synced = false;
#pragma unroll 1
            for (int h = 0; h < 16; h++) {
                if (h == 1) wait_progress(Q_DELAY);
                unsigned n = 0;
                uint32_t qa[4], qb[4];
                while (true) {
                    bool ok = true;
#pragma unroll
                    for (int i = 0; i < 4; i++) ok &= ll_load(g_q + h * 128 + i * 32 + lane, qa[i], qb[i], tag);
                    if (!synced) {
                        asm volatile("bar.sync 2, %0;" ::"n"(NTHREADS) : "memory");
                        if (has_task) mbar_wait(bar_wqdone, 0);
                        synced = true;
                    }
                    if (__all_sync(0xffffffffu, ok)) break;
                    if (++n > SPIN_LIMIT) __trap();
                }
#pragma unroll
                for (int i = 0; i < 4; i++) s_q0[h * 128 + i * 32 + lane] = make_uint2(qa[i], qb[i]);
                __syncwarp();
                if (lane == 0) {
                    if (h == 0) mbar_arrive(bar_q);
                    if (h == 3) mbar_arrive(bar_q2);
                    if (h == 15) mbar_arrive(bar_q3);
                }
            }
        }
        if (has_task) {
            const uint32_t bit = tag & 1u, bitmask = 0u - bit;
            const int qh = slice >> 5;
            const int g = lane >> 2, t4 = lane & 3;
            pol = evict_first_policy();
            float y[7][4];
#pragma unroll
            for (int j = 0; j < 7; j++) { y[j][0] = 0.f; y[j][1] = 0.f; y[j][2] = 0.f; y[j][3] = 0.f; }
            const int h0 = isX ? 8 : 0;
#pragma unroll 1
            for (int h = h0; h < h0 + 8; h++) {
                {
                    uint32_t wf[14][4];
                    if (isX) {
                        wait_progress(h * 4096);
                        if (lane == 0) {
                            asm volatile("fence.proxy.async.shared::cta;" ::: "memory");
                            mbar_expect_tx(bar_wo + (h & 7) * 8, SEG_BYTES);
                            tma3d(sbase + L::SEG, &p.wom[1], (h & 7) * 512 + slice * 8, bar_wo + (h & 7) * 8, pol);
                        }
                        mbar_wait(bar_wo + (h & 7) * 8, 0);
                        load_wo_frags(wf, sbase + L::SEG, lane);
                        __syncwarp();
                    }
                    wait_progress(h < 15 ? (h + 1) * 4096 + MERGE_DELAY : PROG_END);
                    u64 ml[5];
                    uint4 ov[9];
                    const ulonglong2* pml = g_pml + ((h * G + lane) * 2 + qh) * 2;
                    const uint4* pr = g_po + ((size_t)(h * 32 + (slice >> 1)) * G + (lane >> 1)) * 4 + (slice & 1) * 2 + (lane & 1);
                    constexpr int PRS = 16 * 4;
                    const ulonglong2* pml4 = pml + (lane < G - 128 ? 4 * 128 : 0);
                    const uint4* pr8 = pr + (lane < (G - 128) * 2 ? 8 * PRS : 0);
#pragma unroll
                    for (int j = 0; j < 5; j++) ldu64(ml[j], j < 4 ? pml + j * 128 : pml4);
#pragma unroll
                    for (int it = 0; it < 9; it++) ld128(ov[it], it < 8 ? pr + it * PRS : pr8);
                    unsigned n = 0;
                    while (true) {
                        const uint32_t bad = or3(
                            or3(xor_or((uint32_t)(ml[0] >> 32), (uint32_t)(ml[1] >> 32), bitmask),
                                xor_or((uint32_t)(ml[2] >> 32), (uint32_t)(ml[3] >> 32), bitmask),
                                xor_or((uint32_t)(ml[4] >> 32), ov[0].x, bitmask)),
                            or3(xor_or(ov[1].x, ov[2].x, bitmask), xor_or(ov[3].x, ov[4].x, bitmask), xor_or(ov[5].x, ov[6].x, bitmask)),
                            xor_or(ov[7].x, ov[8].x, bitmask));
                        if (__all_sync(0xffffffffu, (bad & 1u) == 0) && (h == 15 || n > 0)) break;
                        if (h != 15) __nanosleep(400);
                        if (++n > SPIN_LIMIT) __trap();
#pragma unroll
                        for (int j = 0; j < 5; j++) ldu64_stale(ml[j], j < 4 ? pml + j * 128 : pml4, bit);
#pragma unroll
                        for (int it = 0; it < 9; it++) ld128_stale(ov[it], it < 8 ? pr + it * PRS : pr8, bit);
                    }
                    float mj[5];
#pragma unroll
                    for (int j = 0; j < 5; j++) mj[j] = __uint_as_float((uint32_t)ml[j]);
                    const float M = warp_max(fmaxf(fmaxf(fmaxf(mj[0], mj[1]), fmaxf(mj[2], mj[3])), mj[4]));
                    float wc[5], Ls = 0.f;
#pragma unroll
                    for (int j = 0; j < 5; j++) {
                        wc[j] = ex2(mj[j] - M);
                        if (j == 4 && lane >= G - 128) wc[j] = 0.f;
                        Ls += wc[j] * __uint_as_float((uint32_t)(ml[j] >> 32));
                    }
                    float a0 = 0.f, a1 = 0.f, a2 = 0.f, a3 = 0.f;
#pragma unroll
                    for (int it = 0; it < 9; it++) {
                        const float wv = __shfl_sync(0xffffffffu, wc[it >> 1], 16 * (it & 1) + (lane >> 1));
                        a0 += wv * __uint_as_float(ov[it].x);
                        a1 += wv * __uint_as_float(ov[it].y);
                        a2 += wv * __uint_as_float(ov[it].z);
                        a3 += wv * __uint_as_float(ov[it].w);
                        if (it == 0) Ls += __shfl_xor_sync(0xffffffffu, Ls, 1);
                    }
                    const bool up = lane & 2;
                    float ax = (up ? a2 : a0) + __shfl_xor_sync(0xffffffffu, up ? a0 : a2, 2);
                    float ay = (up ? a3 : a1) + __shfl_xor_sync(0xffffffffu, up ? a1 : a3, 2);
                    Ls += __shfl_xor_sync(0xffffffffu, Ls, 2);
#pragma unroll
                    for (int o = 4; o <= 16; o <<= 1) {
                        ax += __shfl_xor_sync(0xffffffffu, ax, o);
                        ay += __shfl_xor_sync(0xffffffffu, ay, o);
                        Ls += __shfl_xor_sync(0xffffffffu, Ls, o);
                    }
                    float inv;
                    asm("rcp.approx.ftz.f32 %0, %1;" : "=f"(inv) : "f"(Ls));
                    const uint32_t o2 = pack_bf16(ax * inv, ay * inv);
                    if (isY) {
                        if (lane < 4) s_ofin[h * 4 + lane] = o2;
                        __syncwarp();
                        if (h == 7 && lane == 0) mbar_arrive(bar_ofin);
                    } else {
                        project(y, wf, o2, lane);
                    }
                }
                if (h >= 14) {
                    const uint32_t obit = (h == 15) ? bit : bit ^ 1u;
                    char* dst = reinterpret_cast<char*>(g_ol + ((size_t)(56 + g) * 64 + slice) * 2) + t4 * 8;
#pragma unroll
                    for (int j = 0; j < 7; j++) st64(dst + (size_t)j * 8 * 64 * 32, pt_enc(y[j][0], obit), __float_as_uint(y[j][2]));
                }
            }
            if (cta == 127 && lane == 0) {
                asm volatile("st.relaxed.gpu.global.u32 [%0], %1;" ::"l"(&g_ticket), "r"(0u) : "memory");
                asm volatile("st.relaxed.gpu.global.u32 [%0], %1;" ::"l"(&g_epoch), "r"(tag) : "memory");
            }
        }
    } else {
        uint32_t tag;
        asm volatile("ld.relaxed.gpu.global.u32 %0, [%1];" : "=r"(tag) : "l"(&g_epoch) : "memory");
        const int g = lane >> 2, t4 = lane & 3;
        if (has_task) {
            const int tb = cta >> 6, qs = cta & 63;
            const int r = threadIdx.x >> 3, c8 = threadIdx.x & 7;
            const uint2* xp = reinterpret_cast<const uint2*>(p.x[tb] + 28 * r);
            uint2 xv[7];
#pragma unroll
            for (int i = 0; i < 7; i++)
                asm volatile("ld.global.nc.v2.u32 {%0,%1}, [%2];" : "=r"(xv[i].x), "=r"(xv[i].y) : "l"(xp + i));
            asm volatile("bar.sync 2, %0;" ::"n"(NTHREADS) : "memory");
            mbar_wait(bar_wq, 0);
            const uint4* wv = reinterpret_cast<const uint4*>(smem + L::RING + (NS - 4) * STAGE_BYTES) + 28 * r * 8 + c8;
            float acc[8];
#pragma unroll
            for (int j = 0; j < 8; j++) acc[j] = 0.f;
#pragma unroll
            for (int i = 0; i < 28; i++) {
                const uint32_t xw = (i & 2) ? xv[i >> 2].y : xv[i >> 2].x;
                const float xs = (i & 1) ? bf_hi(xw) : bf_lo(xw);
                const uint4 v = wv[i * 8];
                acc[0] += xs * bf_lo(v.x); acc[1] += xs * bf_hi(v.x);
                acc[2] += xs * bf_lo(v.y); acc[3] += xs * bf_hi(v.y);
                acc[4] += xs * bf_lo(v.z); acc[5] += xs * bf_hi(v.z);
                acc[6] += xs * bf_lo(v.w); acc[7] += xs * bf_hi(v.w);
            }
#pragma unroll
            for (int j = 0; j < 8; j++) {
                acc[j] += __shfl_xor_sync(0xffffffffu, acc[j], 8);
                acc[j] += __shfl_xor_sync(0xffffffffu, acc[j], 16);
            }
            if (lane < 8) {
                float4* d = reinterpret_cast<float4*>(s_red + warp * 64 + lane * 8);
                d[0] = make_float4(acc[0], acc[1], acc[2], acc[3]);
                d[1] = make_float4(acc[4], acc[5], acc[6], acc[7]);
            }
            asm volatile("bar.sync 1, %0;" ::"n"(W * 32) : "memory");
            if (threadIdx.x < 16) {
                const int il = threadIdx.x >> 2;
                float q[4];
#pragma unroll
                for (int k = 0; k < 4; k++) {
                    const int d = 16 * il + 2 * t4 + (k & 1) + 8 * (k >> 1);
                    q[k] = 0.f;
#pragma unroll
                    for (int w = 0; w < W; w++) q[k] += s_red[w * 64 + d];
                }
                ll_store(g_q + ((tb * 16 + (qs >> 2)) * 16 + (qs & 3) * 4 + il) * 4 + t4,
                         pack_bf16(q[0], q[1]), pack_bf16(q[2], q[3]), tag + 1);
            }
            __syncwarp();
            if (lane == 0) mbar_arrive(bar_wqdone);
        } else {
            asm volatile("bar.sync 2, %0;" ::"n"(NTHREADS) : "memory");
        }
        tag += 1;
        const uint32_t bit = tag & 1u;

        float acc[4][4];
#pragma unroll
        for (int i = 0; i < 4; i++) { acc[i][0] = 0.f; acc[i][1] = 0.f; acc[i][2] = 0.f; acc[i][3] = 0.f; }
        float m0 = -INFINITY, m1 = -INFINITY;
        float lacc[4] = {0.f, 0.f, 0.f, 0.f};
        const uint32_t ones[4] = {0x3f803f80u, 0x3f803f80u, 0x3f803f80u, 0x3f803f80u};
        uint32_t qf[16][2];
        int cur = 0;
        const uint32_t krow = (lane & 7) + 8 * ((lane >> 3) & 1), vrow = (lane & 7) + 8 * (lane >> 4);
        const uint32_t koff = krow * 128 + (((lane >> 4) ^ (krow & 7)) << 4);
        const uint32_t voff = TILE_BYTES + vrow * 128 + ((((lane >> 3) & 1) ^ (vrow & 7)) << 4);
        const float SC = 0.0625f * 1.4426950408889634f;
        char* const ydst = reinterpret_cast<char*>(g_ol + ((size_t)(8 * warp + g) * 64 + slice) * 2) + t4 * 8;
        int s = warp;
        uint32_t ph = 0;
        mbar_wait(bar_q, 0);
#pragma unroll
        for (int i = 0; i < 16; i++) {
            const uint2 v = s_q0[((g & 1) * 16 + i) * 4 + t4];
            qf[i][0] = v.x;
            qf[i][1] = v.y;
        }
        while (true) {
            mbar_wait(bar_full + s * 8, ph);
            const int t = s_tk[s];
            const int h = t >> 12;
            if (h != cur) {
                while (cur < h) {
                    float* sl = s_slots + warp * 2 * SLOT_STRIDE + 16 * t4 + 8 * (t4 >> 1) + g;
                    if (lane == 0) *reinterpret_cast<float4*>(s_slotml + warp * 4) = make_float4(m0, lacc[0], m1, lacc[1]);
#pragma unroll
                    for (int j = 0; j < 4; j++) {
                        sl[80 * j] = acc[j][0];
                        sl[80 * j + SLOT_STRIDE] = acc[j][1];
                        sl[80 * j + 8] = acc[j][2];
                        sl[80 * j + 8 + SLOT_STRIDE] = acc[j][3];
                    }
                    uint4* po = g_po + ((size_t)(cur * 32 + 8 * warp + (lane >> 2)) * G + cta) * 4 + (lane & 3);
                    ulonglong2* pml = g_pml + ((cur * G + cta) * 2 + (warp >> 1)) * 2 + lane;
                    asm volatile("bar.sync 1, %0;" ::"n"(W * 32) : "memory");
                    float2 mlw[W];
                    float4 sv[W];
                    float M = -INFINITY;
#pragma unroll
                    for (int w = 0; w < W; w++) {
                        mlw[w] = *reinterpret_cast<const float2*>(s_slotml + w * 4 + (warp & 2));
                        sv[w] = *reinterpret_cast<const float4*>(s_slots + (w * 2 + (warp >> 1)) * SLOT_STRIDE + 160 * (warp & 1) + 4 * lane + (lane & 24));
                        M = fmaxf(M, mlw[w].x);
                    }
                    const float R = (M == -INFINITY) ? 0.f : M;
                    float4 o = make_float4(0.f, 0.f, 0.f, 0.f);
                    float Lw = 0.f;
#pragma unroll
                    for (int w = 0; w < W; w++) {
                        const float f = ex2(mlw[w].x - R);
                        Lw += f * mlw[w].y;
                        o.x += f * sv[w].x; o.y += f * sv[w].y; o.z += f * sv[w].z; o.w += f * sv[w].w;
                    }
                    st128(po, pt_enc(o.x, bit), __float_as_uint(o.y), __float_as_uint(o.z), __float_as_uint(o.w));
                    const bool mlwriter = !(warp & 1) && lane < 2;
                    if (mlwriter) ll_store(pml, __float_as_uint(M), __float_as_uint(M), pt_enc(Lw, bit));
                    if (cur == 13) {
                        st128(po + 2 * 32 * G * 4, bit ^ 1u, 0u, 0u, 0u);
                        if (mlwriter) ll_store(pml + 2 * G * 4, 0u, 0u, bit ^ 1u);
                        if (isY) {
                            st64(ydst, bit ^ 1u, 0u);
                            if (warp < 3) st64(ydst + 4 * 8 * 64 * 32, bit ^ 1u, 0u);
                        }
                    }
#pragma unroll
                    for (int i = 0; i < 4; i++) { acc[i][0] = 0.f; acc[i][1] = 0.f; acc[i][2] = 0.f; acc[i][3] = 0.f; }
                    m0 = -INFINITY; m1 = -INFINITY;
                    lacc[0] = 0.f; lacc[1] = 0.f; lacc[2] = 0.f; lacc[3] = 0.f;
                    cur++;
                    asm volatile("bar.sync 1, %0;" ::"n"(W * 32) : "memory");
                }
                if (h >= 16) break;
                mbar_wait(h > 3 ? bar_q3 : bar_q2, 0);
#pragma unroll
                for (int i = 0; i < 16; i++) {
                    const uint2 v = s_q0[h * 128 + ((g & 1) * 16 + i) * 4 + t4];
                    qf[i][0] = v.x;
                    qf[i][1] = v.y;
                }
            }
            const uint32_t stage = sbase + L::RING + s * STAGE_BYTES;
            float sc[4][4];
#pragma unroll
            for (int c = 0; c < 4; c++) { sc[c][0] = 0.f; sc[c][1] = 0.f; sc[c][2] = 0.f; sc[c][3] = 0.f; }
            const uint32_t kb = stage + koff;
#pragma unroll
            for (int i = 0; i < 16; i++) {
                uint32_t a[4];
                ldsm4(a, (kb ^ ((i & 3) << 5)) + (i >> 2) * 2048);
                mma16816(sc[i & 3], a, qf[i][0], qf[i][1]);
            }
            const uint32_t r01 = pack_bf16((sc[0][0] + sc[1][0]) + (sc[2][0] + sc[3][0]), (sc[0][1] + sc[1][1]) + (sc[2][1] + sc[3][1]));
            const uint32_t r23 = pack_bf16((sc[0][2] + sc[1][2]) + (sc[2][2] + sc[3][2]), (sc[0][3] + sc[1][3]) + (sc[2][3] + sc[3][3]));
            const float s0 = bf_lo(r01) * SC, s1 = bf_hi(r01) * SC, s2 = bf_lo(r23) * SC, s3 = bf_hi(r23) * SC;
            float n0 = fmaxf(s0, s2), n1 = fmaxf(s1, s3);
            if (__any_sync(0xffffffffu, (n0 > m0) | (n1 > m1))) {
                n0 = fmaxf(warp_max(n0), m0);
                n1 = fmaxf(warp_max(n1), m1);
                const float f0 = ex2(m0 - n0), f1 = ex2(m1 - n1);
                m0 = n0; m1 = n1;
                lacc[0] *= f0; lacc[1] *= f1; lacc[2] *= f0; lacc[3] *= f1;
#pragma unroll
                for (int i = 0; i < 4; i++) { acc[i][0] *= f0; acc[i][1] *= f1; acc[i][2] *= f0; acc[i][3] *= f1; }
            }
            const float p0 = ex2(s0 - m0), p1 = ex2(s1 - m1), p2 = ex2(s2 - m0), p3 = ex2(s3 - m1);
            const uint32_t b0 = movtrans(pack_bf16(p0, p1));
            const uint32_t b1 = movtrans(pack_bf16(p2, p3));
            mma16816(lacc, ones, b0, b1);
            mbar_wait(bar_fullv + s * 8, ph);
            const uint32_t vb = stage + voff;
#pragma unroll
            for (int q = 0; q < 4; q++) {
                const uint32_t c0 = ((g >> 1) == q) ? b0 : 0u, c1 = ((g >> 1) == q) ? b1 : 0u;
#pragma unroll
                for (int j = 0; j < 4; j++) {
                    uint32_t a[4];
                    ldsm4t(a, (vb ^ (q << 5)) + j * 2048);
                    mma16816(acc[j], a, c0, c1);
                }
            }
            __syncwarp();
            if (lane == 0) mbar_arrive(bar_empty + s * 8);
            s += W;
            if (s >= NS) { s -= NS; ph ^= 1; }
        }

        if (isY) {
            mbar_wait(bar_ofin, 0);
            float y[7][4];
#pragma unroll
            for (int j = 0; j < 7; j++) { y[j][0] = 0.f; y[j][1] = 0.f; y[j][2] = 0.f; y[j][3] = 0.f; }
            float2* red = reinterpret_cast<float2*>(s_red);
#pragma unroll 1
            for (int k = warp; k < 8; k += W) {
                const uint32_t o2 = s_ofin[k * 4 + t4];
                int ws = s_tk[31] + (k >> 1);
                if (ws >= NS) ws -= NS;
                mbar_wait(bar_wo + k * 8, 0);
                uint32_t wf[14][4];
                load_wo_frags(wf, sbase + L::RING + ws * STAGE_BYTES + (k & 1) * SEG_BYTES, lane);
                project(y, wf, o2, lane);
            }
#pragma unroll
            for (int j = 0; j < 7; j++) red[(warp * 7 + j) * 32 + lane] = make_float2(y[j][0], y[j][2]);
            asm volatile("bar.sync 1, %0;" ::"n"(W * 32) : "memory");
#pragma unroll
            for (int jj = 0; jj < 2; jj++) {
                const int j = warp + 4 * jj;
                if (j < 7) {
                    float vx = 0.f, vy = 0.f;
#pragma unroll
                    for (int w = 0; w < W; w++) {
                        const float2 v = red[(w * 7 + j) * 32 + lane];
                        vx += v.x;
                        vy += v.y;
                    }
                    st64(ydst + jj * 4 * 8 * 64 * 32, pt_enc(vx, bit), __float_as_uint(vy));
                }
            }
        }
        if (isX && slice < 56 && !(warp & 1)) {
            const bool fb = warp < 2;
            const uint32_t bitmask = 0u - bit;
            const uint4* src = g_ol + (size_t)((fb ? 56 : 0) + slice) * 64 * 2 + lane;
            const int et = 2 * (lane & 1) + ((lane >> 1) & 1), es = (lane >> 2) & 1;
            const int col = (fb ? DM : 0) + 64 * (slice >> 3) + 16 * et + 8 * es + (slice & 7);
            __nv_bfloat16* dst = p.out + col;
            unsigned n = 0;
            while (true) {
                uint4 v[4];
#pragma unroll
                for (int i = 0; i < 4; i++) ld2x64(v[i], src + i * 32);
                const uint32_t bad = or3(xor_or(v[0].x, v[0].z, bitmask), xor_or(v[1].x, v[1].z, bitmask),
                                         xor_or(v[2].x, v[2].z, bitmask)) | xor_or(v[3].x, v[3].z, bitmask);
                const bool done = __all_sync(0xffffffffu, (bad & 1u) == 0);
                const float a0 = (__uint_as_float(v[0].x) + __uint_as_float(v[1].x)) + (__uint_as_float(v[2].x) + __uint_as_float(v[3].x));
                const float a1 = (__uint_as_float(v[0].y) + __uint_as_float(v[1].y)) + (__uint_as_float(v[2].y) + __uint_as_float(v[3].y));
                const float a2 = (__uint_as_float(v[0].z) + __uint_as_float(v[1].z)) + (__uint_as_float(v[2].z) + __uint_as_float(v[3].z));
                const float a3 = (__uint_as_float(v[0].w) + __uint_as_float(v[1].w)) + (__uint_as_float(v[2].w) + __uint_as_float(v[3].w));
                if (done || n == 0) {
                    const bool u1 = lane & 2, u2 = lane & 4;
                    const float bx = (u1 ? a2 : a0) + __shfl_xor_sync(0xffffffffu, u1 ? a0 : a2, 2);
                    const float by = (u1 ? a3 : a1) + __shfl_xor_sync(0xffffffffu, u1 ? a1 : a3, 2);
                    float c = (u2 ? by : bx) + __shfl_xor_sync(0xffffffffu, u2 ? bx : by, 4);
                    c += __shfl_xor_sync(0xffffffffu, c, 8);
                    c += __shfl_xor_sync(0xffffffffu, c, 16);
                    if (done && lane < 8) *dst = __float2bfloat16(c);
                    if (done) break;
                }
                if (++n > SPIN_LIMIT) __trap();
            }
        }
    }
}

constexpr int FB_SPLIT = 32;
__device__ float g_fq[2 * 4096];
__device__ float g_fp[16 * FB_SPLIT * 8 * 2 * 264];

__global__ void fb_q_kernel(const __nv_bfloat16* x, const __nv_bfloat16* wq, int b) {
    const int n = blockIdx.x * blockDim.x + threadIdx.x;
    float a = 0.f;
    for (int k = 0; k < DM; k++) a += __bfloat162float(x[k]) * __bfloat162float(wq[(size_t)k * 4096 + n]);
    g_fq[b * 4096 + n] = __bfloat162float(__float2bfloat16(a));
}
__global__ void fb_attn_kernel(const uint4* k, const uint4* v, int b) {
    const int hk = blockIdx.y, warp = threadIdx.x >> 5, lane = threadIdx.x & 31;
    float q[2][8], o[2][8], m[2] = {-INFINITY, -INFINITY}, l[2] = {0.f, 0.f};
    for (int h = 0; h < 2; h++)
        for (int j = 0; j < 8; j++) { q[h][j] = g_fq[b * 4096 + (hk * 2 + h) * 256 + lane * 8 + j]; o[h][j] = 0.f; }
    const int n = 65536 / FB_SPLIT / 8;
    const size_t row0 = (size_t)hk * 65536 + (size_t)(blockIdx.x * 8 + warp) * n;
    for (int i = 0; i < n; i++) {
        const uint4 kk = k[(row0 + i) * 32 + lane], vv = v[(row0 + i) * 32 + lane];
        const float kf[8] = {bf_lo(kk.x), bf_hi(kk.x), bf_lo(kk.y), bf_hi(kk.y), bf_lo(kk.z), bf_hi(kk.z), bf_lo(kk.w), bf_hi(kk.w)};
        const float vf[8] = {bf_lo(vv.x), bf_hi(vv.x), bf_lo(vv.y), bf_hi(vv.y), bf_lo(vv.z), bf_hi(vv.z), bf_lo(vv.w), bf_hi(vv.w)};
#pragma unroll
        for (int h = 0; h < 2; h++) {
            float s = 0.f;
#pragma unroll
            for (int j = 0; j < 8; j++) s += q[h][j] * kf[j];
            for (int d = 16; d >= 1; d >>= 1) s += __shfl_xor_sync(0xffffffffu, s, d);
            s = __bfloat162float(__float2bfloat16(s)) * (0.0625f * 1.4426950408889634f);
            const float mn = fmaxf(m[h], s), f = ex2(m[h] - mn), pr = ex2(s - mn);
            m[h] = mn;
            l[h] = l[h] * f + pr;
#pragma unroll
            for (int j = 0; j < 8; j++) o[h][j] = o[h][j] * f + pr * vf[j];
        }
    }
    for (int h = 0; h < 2; h++) {
        float* d = g_fp + ((((size_t)(b * 8 + hk) * FB_SPLIT + blockIdx.x) * 8 + warp) * 2 + h) * 264;
        for (int j = 0; j < 8; j++) d[lane * 8 + j] = o[h][j];
        if (lane == 0) { d[256] = m[h]; d[257] = l[h]; }
    }
}
__global__ void fb_merge_kernel() {
    const int hq = blockIdx.x;
    const float* base = g_fp + ((size_t)(hq >> 1) * FB_SPLIT * 8 * 2 + (hq & 1)) * 264;
    float M = -INFINITY, Ls = 0.f, a = 0.f;
    for (int i = 0; i < FB_SPLIT * 8; i++) M = fmaxf(M, base[(size_t)i * 528 + 256]);
    for (int i = 0; i < FB_SPLIT * 8; i++) {
        const float w = ex2(base[(size_t)i * 528 + 256] - M);
        Ls += w * base[(size_t)i * 528 + 257];
        a += w * base[(size_t)i * 528 + threadIdx.x];
    }
    g_fq[hq * 256 + threadIdx.x] = __bfloat162float(__float2bfloat16(a / Ls));
}
__global__ void fb_out_kernel(const __nv_bfloat16* wo, __nv_bfloat16* out, int b) {
    const int n = blockIdx.x * 64 + threadIdx.x;
    float a = 0.f;
    for (int k = 0; k < 4096; k++) a += g_fq[b * 4096 + k] * __bfloat162float(wo[(size_t)k * DM + n]);
    out[b * DM + n] = __float2bfloat16(a);
}

typedef CUresult (*EncodeFn)(CUtensorMap*, CUtensorMapDataType, cuuint32_t, void*, const cuuint64_t*, const cuuint64_t*,
                             const cuuint32_t*, const cuuint32_t*, CUtensorMapInterleave, CUtensorMapSwizzle,
                             CUtensorMapL2promotion, CUtensorMapFloatOOBfill);

void encode_kv(EncodeFn enc, CUtensorMap* m, const void* ptr) {
    cuuint64_t gd[3] = {64, 8ull * 65536ull, 4};
    cuuint64_t gs[2] = {512, 128};
    cuuint32_t box[3] = {64, 16, 4};
    cuuint32_t es[3] = {1, 1, 1};
    enc(m, CU_TENSOR_MAP_DATA_TYPE_BFLOAT16, 3, const_cast<void*>(ptr), gd, gs, box, es, CU_TENSOR_MAP_INTERLEAVE_NONE,
        CU_TENSOR_MAP_SWIZZLE_128B, CU_TENSOR_MAP_L2_PROMOTION_L2_256B, CU_TENSOR_MAP_FLOAT_OOB_FILL_NONE);
}

void encode_wo(EncodeFn enc, CUtensorMap* m, const void* ptr) {
    cuuint64_t gd[3] = {64, 4096, 7};
    cuuint64_t gs[2] = {DM * 2, 128};
    cuuint32_t box[3] = {64, 8, 7};
    cuuint32_t es[3] = {1, 1, 1};
    enc(m, CU_TENSOR_MAP_DATA_TYPE_BFLOAT16, 3, const_cast<void*>(ptr), gd, gs, box, es, CU_TENSOR_MAP_INTERLEAVE_NONE,
        CU_TENSOR_MAP_SWIZZLE_128B, CU_TENSOR_MAP_L2_PROMOTION_L2_128B, CU_TENSOR_MAP_FLOAT_OOB_FILL_NONE);
}

void encode_wq(EncodeFn enc, CUtensorMap* m, const void* ptr) {
    cuuint64_t gd[2] = {4096, 448};
    cuuint64_t gs[1] = {8192};
    cuuint32_t box[2] = {64, 224};
    cuuint32_t es[2] = {1, 1};
    enc(m, CU_TENSOR_MAP_DATA_TYPE_BFLOAT16, 2, const_cast<void*>(ptr), gd, gs, box, es, CU_TENSOR_MAP_INTERLEAVE_NONE,
        CU_TENSOR_MAP_SWIZZLE_NONE, CU_TENSOR_MAP_L2_PROMOTION_L2_128B, CU_TENSOR_MAP_FLOAT_OOB_FILL_NONE);
}

}

extern "C" void kernel_launch(void* const* d_in, const int* in_sizes, int n_in, void* d_out, int out_size) {
    (void)in_sizes; (void)n_in; (void)out_size;
    static EncodeFn enc = nullptr;
    static int mode = -1;
    if (mode < 0) {
        cudaDriverEntryPointQueryResult qr;
        void* fn = nullptr;
        cudaGetDriverEntryPoint("cuTensorMapEncodeTiled", &fn, cudaEnableDefault, &qr);
        enc = (EncodeFn)fn;
        int dev = 0, sms = 0, occ = 0;
        cudaGetDevice(&dev);
        cudaDeviceGetAttribute(&sms, cudaDevAttrMultiProcessorCount, dev);
        const bool attr_ok =
            cudaFuncSetAttribute(fused_decode_kernel, cudaFuncAttributeMaxDynamicSharedMemorySize, L::SIZE) == cudaSuccess;
        if (attr_ok) cudaOccupancyMaxActiveBlocksPerMultiprocessor(&occ, fused_decode_kernel, NTHREADS, L::SIZE);
        mode = (enc != nullptr && attr_ok && sms * occ >= G) ? 1 : 0;
        (void)cudaGetLastError();
    }
    if (mode == 1) {
        Params p;
        for (int b = 0; b < 2; b++) {
            p.x[b] = (const __nv_bfloat16*)d_in[5 * b + 0];
            encode_kv(enc, &p.km[b], d_in[5 * b + 1]);
            encode_kv(enc, &p.vm[b], d_in[5 * b + 2]);
            encode_wq(enc, &p.wqm[b], d_in[5 * b + 3]);
            encode_wo(enc, &p.wom[b], d_in[5 * b + 4]);
        }
        p.out = (__nv_bfloat16*)d_out;
        fused_decode_kernel<<<G, NTHREADS, L::SIZE>>>(p);
    } else {
        for (int b = 0; b < 2; b++) {
            fb_q_kernel<<<16, 256>>>((const __nv_bfloat16*)d_in[5 * b], (const __nv_bfloat16*)d_in[5 * b + 3], b);
            fb_attn_kernel<<<dim3(FB_SPLIT, 8), 256>>>((const uint4*)d_in[5 * b + 1], (const uint4*)d_in[5 * b + 2], b);
        }
        fb_merge_kernel<<<32, 256>>>();
        for (int b = 0; b < 2; b++)
            fb_out_kernel<<<7, 64>>>((const __nv_bfloat16*)d_in[5 * b + 4], (__nv_bfloat16*)d_out, b);
    }
}
```

```cpp
#include <cuda_runtime.h>
#include <cuda_bf16.h>
#include <cuda.h>
#include <stdint.h>

namespace {

constexpr int G = 132;
constexpr int W = 4;
constexpr int NTHREADS = (W + 2) * 32;
constexpr int TILE_BYTES = 8192;
constexpr int STAGE_BYTES = 2 * TILE_BYTES;
constexpr int TOTAL = 65536;
constexpr int DM = 448;
constexpr int SEG_BYTES = 8 * DM * 2;
constexpr int SLOT_STRIDE = 320;
constexpr int PROG_END = 1 << 30;
constexpr int NS = 12;
constexpr int K0 = 3;
constexpr int Q_DELAY = 1500;
constexpr int MERGE_DELAY = 2500;
constexpr int CAP = 4;
constexpr int XSTOP = 1800;
constexpr int WO_CAP = 4;
constexpr unsigned SPIN_LIMIT = 1u << 22;

struct Params {
    const __nv_bfloat16* x[2];
    __nv_bfloat16* out;
    CUtensorMap km[2];
    CUtensorMap vm[2];
    CUtensorMap wqm[2];
    CUtensorMap wom[2];
};

typedef unsigned long long u64;

__device__ __align__(128) unsigned int g_epoch;
__device__ __align__(128) unsigned int g_ticket;
__device__ __align__(128) ulonglong2 g_q[16 * 2 * 16 * 4];
__device__ __align__(128) uint4 g_po[16 * 128 * G];
__device__ __align__(128) uint4 g_ol[2 * 56 * 64 * 2];

__device__ __forceinline__ uint32_t smem_u32(const void* p) { return (uint32_t)__cvta_generic_to_shared(p); }
__device__ __forceinline__ void mbar_init(uint32_t bar, uint32_t cnt) {
    asm volatile("mbarrier.init.shared::cta.b64 [%0], %1;" ::"r"(bar), "r"(cnt) : "memory");
}
__device__ __forceinline__ void mbar_expect_tx(uint32_t bar, uint32_t bytes) {
    asm volatile("mbarrier.arrive.expect_tx.shared::cta.b64 _, [%0], %1;" ::"r"(bar), "r"(bytes) : "memory");
}
__device__ __forceinline__ void mbar_arrive(uint32_t bar) {
    asm volatile("mbarrier.arrive.shared::cta.b64 _, [%0];" ::"r"(bar) : "memory");
}
__device__ __forceinline__ bool mbar_try(uint32_t bar, uint32_t parity) {
    uint32_t ok;
    asm volatile("{\n.reg .pred p;\nmbarrier.try_wait.parity.shared::cta.b64 p, [%1], %2;\nselp.u32 %0, 1, 0, p;\n}"
                 : "=r"(ok) : "r"(bar), "r"(parity) : "memory");
    return ok != 0;
}
__device__ __forceinline__ void mbar_wait(uint32_t bar, uint32_t parity) {
    unsigned n = 0;
    while (!mbar_try(bar, parity)) {
        if (++n > SPIN_LIMIT) __trap();
    }
}
__device__ __forceinline__ void tma3d(uint32_t dst, const CUtensorMap* m, int row, uint32_t bar, uint64_t pol) {
    asm volatile(
        "cp.async.bulk.tensor.3d.shared::cluster.global.mbarrier::complete_tx::bytes.L2::cache_hint "
        "[%0], [%1, {%3, %4, %3}], [%2], %5;" ::"r"(dst), "l"(m), "r"(bar), "r"(0), "r"(row), "l"(pol)
        : "memory");
}
__device__ __forceinline__ uint64_t evict_first_policy() {
    uint64_t pol;
    asm volatile("createpolicy.fractional.L2::evict_first.b64 %0, 1.0;" : "=l"(pol));
    return pol;
}
__device__ __forceinline__ void ldsm4(uint32_t (&r)[4], uint32_t addr) {
    asm volatile("ldmatrix.sync.aligned.m8n8.x4.shared.b16 {%0,%1,%2,%3}, [%4];"
                 : "=r"(r[0]), "=r"(r[1]), "=r"(r[2]), "=r"(r[3]) : "r"(addr) : "memory");
}
__device__ __forceinline__ void ldsm4t(uint32_t (&r)[4], uint32_t addr) {
    asm volatile("ldmatrix.sync.aligned.m8n8.x4.trans.shared.b16 {%0,%1,%2,%3}, [%4];"
                 : "=r"(r[0]), "=r"(r[1]), "=r"(r[2]), "=r"(r[3]) : "r"(addr) : "memory");
}
__device__ __forceinline__ void mma16816(float (&c)[4], const uint32_t (&a)[4], uint32_t b0, uint32_t b1) {
    asm volatile("mma.sync.aligned.m16n8k16.row.col.f32.bf16.bf16.f32 {%0,%1,%2,%3}, {%4,%5,%6,%7}, {%8,%9}, {%0,%1,%2,%3};"
                 : "+f"(c[0]), "+f"(c[1]), "+f"(c[2]), "+f"(c[3])
                 : "r"(a[0]), "r"(a[1]), "r"(a[2]), "r"(a[3]), "r"(b0), "r"(b1));
}
__device__ __forceinline__ uint32_t movtrans(uint32_t a) {
    uint32_t d;
    asm volatile("movmatrix.sync.aligned.m8n8.trans.b16 %0, %1;" : "=r"(d) : "r"(a));
    return d;
}
__device__ __forceinline__ float ex2(float x) {
    float y;
    asm("ex2.approx.ftz.f32 %0, %1;" : "=f"(y) : "f"(x));
    return y;
}
__device__ __forceinline__ uint32_t pack_bf16(float lo, float hi) {
    uint32_t d;
    asm("cvt.rn.bf16x2.f32 %0, %1, %2;" : "=r"(d) : "f"(hi), "f"(lo));
    return d;
}
__device__ __forceinline__ float bf_lo(uint32_t v) { return __uint_as_float(v << 16); }
__device__ __forceinline__ float bf_hi(uint32_t v) { return __uint_as_float(v & 0xffff0000u); }
__device__ __forceinline__ float warp_max(float v) {
    int k = __float_as_int(v);
    k ^= (k >> 31) & 0x7fffffff;
    k = __reduce_max_sync(0xffffffffu, k);
    k ^= (k >> 31) & 0x7fffffff;
    return __int_as_float(k);
}

__device__ __forceinline__ u64 ll_word(uint32_t v, uint32_t tag) { return ((u64)tag << 32) | v; }
__device__ __forceinline__ void ll_store(ulonglong2* p, uint32_t a, uint32_t b, uint32_t tag) {
    asm volatile("st.relaxed.gpu.global.v2.b64 [%0], {%1, %2};" ::"l"(p), "l"(ll_word(a, tag)), "l"(ll_word(b, tag)) : "memory");
}
__device__ __forceinline__ bool ll_ok(u64 x, u64 y, uint32_t tag) {
    return ((uint32_t)(x >> 32) == tag) & ((uint32_t)(y >> 32) == tag);
}
__device__ __forceinline__ uint32_t pt_enc(float v, uint32_t bit) { return (__float_as_uint(v) & ~1u) | bit; }
__device__ __forceinline__ uint32_t xor_or(uint32_t a, uint32_t b, uint32_t m) {
    uint32_t d;
    asm("lop3.b32 %0, %1, %2, %3, 0x7e;" : "=r"(d) : "r"(a), "r"(b), "r"(m));
    return d;
}
__device__ __forceinline__ uint32_t or3(uint32_t a, uint32_t b, uint32_t c) {
    uint32_t d;
    asm("lop3.b32 %0, %1, %2, %3, 0xfe;" : "=r"(d) : "r"(a), "r"(b), "r"(c));
    return d;
}
__device__ __forceinline__ void st128(uint4* p, uint32_t a, uint32_t b, uint32_t c, uint32_t d) {
    asm volatile("{\n.reg .b128 t;\n.reg .b64 lo, hi;\nmov.b64 lo, {%1, %2};\nmov.b64 hi, {%3, %4};\nmov.b128 t, {lo, hi};\n"
                 "st.relaxed.gpu.global.b128 [%0], t;\n}" ::"l"(p), "r"(a), "r"(b), "r"(c), "r"(d) : "memory");
}
__device__ __forceinline__ void ld128(uint4& v, const uint4* p) {
    asm volatile("{\n.reg .b128 t;\n.reg .b64 lo, hi;\nld.relaxed.gpu.global.b128 t, [%4];\nmov.b128 {lo, hi}, t;\n"
                 "mov.b64 {%0, %1}, lo;\nmov.b64 {%2, %3}, hi;\n}"
                 : "=r"(v.x), "=r"(v.y), "=r"(v.z), "=r"(v.w) : "l"(p) : "memory");
}
__device__ __forceinline__ void ld128_stale(uint4& v, const uint4* p, uint32_t bit) {
    asm volatile("{\n.reg .pred p;\n.reg .b32 u;\n.reg .b128 t;\n.reg .b64 lo, hi;\nand.b32 u, %0, 1;\nsetp.ne.u32 p, u, %5;\n"
                 "mov.b64 lo, {%0, %1};\nmov.b64 hi, {%2, %3};\nmov.b128 t, {lo, hi};\n"
                 "@p ld.relaxed.gpu.global.b128 t, [%4];\nmov.b128 {lo, hi}, t;\nmov.b64 {%0, %1}, lo;\nmov.b64 {%2, %3}, hi;\n}"
                 : "+r"(v.x), "+r"(v.y), "+r"(v.z), "+r"(v.w) : "l"(p), "r"(bit) : "memory");
}
__device__ __forceinline__ void st64(void* p, uint32_t a, uint32_t b) {
    asm volatile("{\n.reg .b64 t;\nmov.b64 t, {%1, %2};\nst.relaxed.gpu.global.b64 [%0], t;\n}" ::"l"(p), "r"(a), "r"(b) : "memory");
}
__device__ __forceinline__ void ld2x64(uint4& v, const uint4* p) {
    asm volatile("{\n.reg .b64 lo, hi;\nld.relaxed.gpu.global.v2.b64 {lo, hi}, [%4];\nmov.b64 {%0, %1}, lo;\nmov.b64 {%2, %3}, hi;\n}"
                 : "=r"(v.x), "=r"(v.y), "=r"(v.z), "=r"(v.w) : "l"(p) : "memory");
}
__device__ __forceinline__ void mma1688(float (&c)[4], uint32_t a0, uint32_t a1, uint32_t b0) {
    asm volatile("mma.sync.aligned.m16n8k8.row.col.f32.bf16.bf16.f32 {%0,%1,%2,%3}, {%4,%5}, {%6}, {%0,%1,%2,%3};"
                 : "+f"(c[0]), "+f"(c[1]), "+f"(c[2]), "+f"(c[3]) : "r"(a0), "r"(a1), "r"(b0));
}
__device__ __forceinline__ bool ll_load(const ulonglong2* p, uint32_t& a, uint32_t& b, uint32_t tag) {
    u64 x, y;
    asm volatile("ld.relaxed.gpu.global.v2.b64 {%0, %1}, [%2];" : "=l"(x), "=l"(y) : "l"(p) : "memory");
    a = (uint32_t)x;
    b = (uint32_t)y;
    return ll_ok(x, y, tag);
}

__device__ __forceinline__ void load_wo_frags(uint32_t (&wf)[14][4], uint32_t seg, int lane) {
    const uint32_t row = 4 * ((lane >> 1) & 1) + 2 * ((lane >> 2) & 1) + (lane & 1);
    const uint32_t a = seg + row * 128 + ((((uint32_t)lane >> 3) ^ row) << 4);
#pragma unroll
    for (int x = 0; x < 14; x++) ldsm4t(wf[x], (a ^ ((x & 1) << 6)) + (x >> 1) * 1024);
}
__device__ __forceinline__ void project(float (&y)[7][4], const uint32_t (&wf)[14][4], uint32_t o2, int lane) {
#pragma unroll
    for (int q = 0; q < 4; q++) {
        const uint32_t bq = ((lane >> 2) == 2 * q) ? o2 : 0u;
#pragma unroll
        for (int j = 0; j < 7; j++) {
            const int i = 4 * j + q;
            mma1688(y[j], wf[i >> 1][2 * (i & 1)], wf[i >> 1][2 * (i & 1) + 1], bq);
        }
    }
}

__device__ __forceinline__ float unit_lse(const uint4& v) {
    return __uint_as_float(__byte_perm(__byte_perm(v.x, v.y, 0x0040), __byte_perm(v.z, v.w, 0x0040), 0x5410));
}
__device__ __forceinline__ uint32_t merge_slice(int h, int slice, uint32_t bit, int lane) {
    const uint32_t bitmask = 0u - bit;
    uint4 ov[9];
    const uint4* pr = g_po + ((size_t)(h * 16 + (slice >> 2)) * G + (lane >> 1)) * 8 + (slice & 3) * 2 + (lane & 1);
    constexpr int PRS = 16 * 8;
    const uint4* pr8 = pr + (lane < (G - 128) * 2 ? 8 * PRS : 0);
#pragma unroll
    for (int it = 0; it < 9; it++) ld128(ov[it], it < 8 ? pr + it * PRS : pr8);
    unsigned n = 0;
    while (true) {
        const uint32_t bad = or3(or3(xor_or(ov[0].x, ov[1].x, bitmask), xor_or(ov[2].x, ov[3].x, bitmask), xor_or(ov[4].x, ov[5].x, bitmask)),
                                 xor_or(ov[6].x, ov[7].x, bitmask), ov[8].x ^ bitmask);
        if (__all_sync(0xffffffffu, (bad & 1u) == 0)) break;
        if (h != 15) __nanosleep(400);
        if (++n > SPIN_LIMIT) __trap();
#pragma unroll
        for (int it = 0; it < 9; it++) ld128_stale(ov[it], it < 8 ? pr + it * PRS : pr8, bit);
    }
    float e[9];
#pragma unroll
    for (int it = 0; it < 9; it++) e[it] = unit_lse(ov[it]);
    const float M = warp_max(fmaxf(fmaxf(fmaxf(fmaxf(e[0], e[1]), fmaxf(e[2], e[3])), fmaxf(fmaxf(e[4], e[5]), fmaxf(e[6], e[7]))), e[8]));
    float Ls = 0.f, a0 = 0.f, a1 = 0.f, a2 = 0.f, a3 = 0.f;
#pragma unroll
    for (int it = 0; it < 9; it++) {
        float wv = ex2(e[it] - M);
        if (it == 8 && lane >= (G - 128) * 2) wv = 0.f;
        Ls += wv;
        a0 += wv * __uint_as_float(ov[it].x);
        a1 += wv * __uint_as_float(ov[it].y);
        a2 += wv * __uint_as_float(ov[it].z);
        a3 += wv * __uint_as_float(ov[it].w);
    }
    const bool up = lane & 2;
    float ax = (up ? a2 : a0) + __shfl_xor_sync(0xffffffffu, up ? a0 : a2, 2);
    float ay = (up ? a3 : a1) + __shfl_xor_sync(0xffffffffu, up ? a1 : a3, 2);
    Ls += __shfl_xor_sync(0xffffffffu, Ls, 2);
#pragma unroll
    for (int o = 4; o <= 16; o <<= 1) {
        ax += __shfl_xor_sync(0xffffffffu, ax, o);
        ay += __shfl_xor_sync(0xffffffffu, ay, o);
        Ls += __shfl_xor_sync(0xffffffffu, Ls, o);
    }
    float inv;
    asm("rcp.approx.ftz.f32 %0, %1;" : "=f"(inv) : "f"(Ls));
    return pack_bf16(ax * inv, ay * inv);
}

struct L {
    static constexpr int RING = 0;
    static constexpr int SEG = NS * STAGE_BYTES;
    static constexpr int SLOTS = SEG + SEG_BYTES;
    static constexpr int Q0 = SLOTS + W * 2 * SLOT_STRIDE * 4;
    static constexpr int SLOTML = Q0 + 16 * 128 * 8;
    static constexpr int OFIN = SLOTML + W * 16;
    static constexpr int TK = OFIN + 32 * 4;
    static constexpr int BARS = TK + 32 * 4;
    static constexpr int NBARS = 3 * NS + 7 + 8;
    static constexpr int SIZE = BARS + NBARS * 8;
};

__global__ void __launch_bounds__(NTHREADS, 1) fused_decode_kernel(const __grid_constant__ Params p) {
    extern __shared__ __align__(1024) unsigned char smem_raw[];
    static_assert(NS % W == 0 && K0 >= 2 && K0 <= NS - 4 && W == 4, "geometry");
    unsigned char* smem = smem_raw;
    const uint32_t sbase = smem_u32(smem);
    const int warp = threadIdx.x >> 5, lane = threadIdx.x & 31;
    const int cta = blockIdx.x;
    const bool has_task = cta < 128;
    const bool isX = has_task && cta >= 112;
    const int h0 = 2 * (cta >> 4), sl0 = 4 * (cta & 15);

    const uint32_t bar_full = sbase + L::BARS;
    const uint32_t bar_fullv = bar_full + NS * 8;
    const uint32_t bar_empty = bar_fullv + NS * 8;
    const uint32_t bar_wq = bar_empty + NS * 8;
    const uint32_t bar_q = bar_wq + 8;
    const uint32_t bar_q2 = bar_q + 8;
    const uint32_t bar_q3 = bar_q2 + 8;
    const uint32_t bar_ofin = bar_q3 + 8;
    const uint32_t bar_wo = bar_ofin + 8;
    const uint32_t bar_wqdone = bar_wo + 64;
    const uint32_t bar_pub = bar_wqdone + 8;
    volatile int* s_tk = reinterpret_cast<volatile int*>(smem + L::TK);
    float* s_slots = reinterpret_cast<float*>(smem + L::SLOTS);
    float* s_slotml = reinterpret_cast<float*>(smem + L::SLOTML);
    float* s_red = reinterpret_cast<float*>(smem + L::SEG);
    uint32_t* s_ofin = reinterpret_cast<uint32_t*>(smem + L::OFIN);
    uint2* s_q0 = reinterpret_cast<uint2*>(smem + L::Q0);

    uint64_t pol = 0;
    auto issue = [&](int s, int t) {
        s_tk[s] = t;
        s_tk[30] = t;
        const uint32_t dst = sbase + L::RING + s * STAGE_BYTES;
        const int b = t >> 15, row = (t & 32767) << 4;
        mbar_expect_tx(bar_full + s * 8, TILE_BYTES);
        tma3d(dst, &p.km[b], row, bar_full + s * 8, pol);
        mbar_expect_tx(bar_fullv + s * 8, TILE_BYTES);
        tma3d(dst + TILE_BYTES, &p.vm[b], row, bar_fullv + s * 8, pol);
    };
    if (threadIdx.x == W * 32) {
        mbar_init(bar_full, 1);
        mbar_init(bar_fullv, 1);
        asm volatile("fence.mbarrier_init.release.cluster;" ::: "memory");
        pol = evict_first_policy();
        mbar_expect_tx(bar_full, TILE_BYTES);
        tma3d(sbase + L::RING, &p.km[0], cta << 4, bar_full, pol);
        mbar_expect_tx(bar_fullv, TILE_BYTES);
        tma3d(sbase + L::RING + TILE_BYTES, &p.vm[0], cta << 4, bar_fullv, pol);
        s_tk[0] = cta;
        mbar_init(bar_wq, 1);
#pragma unroll
        for (int i = 1; i < K0; i++) { mbar_init(bar_full + i * 8, 1); mbar_init(bar_fullv + i * 8, 1); }
        asm volatile("fence.mbarrier_init.release.cluster;" ::: "memory");
        if (has_task) {
            mbar_expect_tx(bar_wq, 448 * 128);
#pragma unroll
            for (int i = 0; i < 2; i++)
                asm volatile(
                    "cp.async.bulk.tensor.2d.shared::cluster.global.mbarrier::complete_tx::bytes.L2::cache_hint "
                    "[%0], [%1, {%3, %4}], [%2], %5;" ::"r"(sbase + L::RING + (NS - 4) * STAGE_BYTES + i * 224 * 128),
                    "l"(&p.wqm[cta >> 6]), "r"(bar_wq), "r"((cta & 63) * 64), "r"(i * 224), "l"(pol) : "memory");
        }
#pragma unroll
        for (int i = 1; i < K0; i++) issue(i, cta + G * i);
#pragma unroll
        for (int i = 0; i < L::NBARS; i++)
            if (!(i < K0 || (i >= NS && i < NS + K0) || i == 3 * NS)) mbar_init(bar_full + i * 8, i >= L::NBARS - 2 ? W : 1);
        asm volatile("fence.mbarrier_init.release.cluster;" ::: "memory");
    }

    if (warp == W) {
        __syncwarp();
        asm volatile("bar.arrive 2, %0;" ::"n"(NTHREADS) : "memory");
        if (lane == 0) {
            asm volatile("prefetch.tensormap [%0];" ::"l"(&p.km[1]) : "memory");
            asm volatile("prefetch.tensormap [%0];" ::"l"(&p.vm[1]) : "memory");
            asm volatile("prefetch.tensormap [%0];" ::"l"(&p.wom[(cta >> 6) & 1]) : "memory");
        }
        pol = evict_first_policy();
        int s = K0, cnt = K0, t = 0;
        uint32_t ph = 1;
        bool first_lap = has_task;
        while (true) {
            if (cnt >= CAP) {
                int sd = s - CAP;
                uint32_t pd = ph ^ 1;
                if (sd < 0) { sd += NS; pd ^= 1; }
                mbar_wait(bar_full + sd * 8, pd);
            }
            cnt++;
            if (isX && t >= TOTAL - XSTOP) break;
            unsigned v = 0;
            if (lane == 0) asm volatile("atom.relaxed.gpu.global.inc.u32 %0, [%1], 0x7fffffff;" : "=r"(v) : "l"(&g_ticket) : "memory");
            mbar_wait(bar_empty + s * 8, ph);
            if (first_lap && s == NS - 4) { mbar_wait(bar_wqdone, 0); first_lap = false; }
            t = (int)__shfl_sync(0xffffffffu, v, 0) + G * K0;
            if (t >= TOTAL) break;
            const uint32_t dst = sbase + L::RING + s * STAGE_BYTES;
            const int b = t >> 15;
            asm volatile(
                "{\n.reg .pred p;\nelect.sync _|p, 0xffffffff;\n"
                "@p st.volatile.shared.u32 [%8], %9;\n"
                "@p st.volatile.shared.u32 [%10], %9;\n"
                "@p mbarrier.arrive.expect_tx.shared::cta.b64 _, [%3], 8192;\n"
                "@p cp.async.bulk.tensor.3d.shared::cluster.global.mbarrier::complete_tx::bytes.L2::cache_hint "
                "[%0], [%1, {%5, %6, %5}], [%3], %7;\n"
                "@p mbarrier.arrive.expect_tx.shared::cta.b64 _, [%4], 8192;\n"
                "@p cp.async.bulk.tensor.3d.shared::cluster.global.mbarrier::complete_tx::bytes.L2::cache_hint "
                "[%11], [%2, {%5, %6, %5}], [%4], %7;\n}"
                ::"r"(dst), "l"(&p.km[b]), "l"(&p.vm[b]), "r"(bar_full + s * 8), "r"(bar_fullv + s * 8), "r"(0),
                  "r"((t & 32767) << 4), "l"(pol), "r"(sbase + L::TK + s * 4), "r"(t), "r"(sbase + L::TK + 30 * 4),
                  "r"(dst + TILE_BYTES) : "memory");
            if (++s == NS) { s = 0; ph ^= 1; }
        }
        if (lane == 0) {
            s_tk[30] = PROG_END;
            s_tk[31] = s;
        }
        __syncwarp();
        if (lane < W) {
            int sj = s + lane;
            uint32_t pj = ph;
            if (sj >= NS) { sj -= NS; pj ^= 1; }
            mbar_wait(bar_empty + sj * 8, pj);
            s_tk[sj] = TOTAL;
            mbar_arrive(bar_full + sj * 8);
        }
        __syncwarp();
        if (has_task) {
            mbar_wait(bar_wqdone, 0);
            {
                int sd = s - 2;
                uint32_t pd = ph ^ 1;
                if (sd < 0) { sd += NS; pd ^= 1; }
                mbar_wait(bar_full + sd * 8, pd);
            }
#pragma unroll
            for (int k = 0; k < 8; k++) {
                int ws = s + (k >> 1);
                if (ws >= NS) ws -= NS;
                if (k >= WO_CAP) mbar_wait(bar_wo + (k - WO_CAP) * 8, 0);
                asm volatile(
                    "{\n.reg .pred p;\nelect.sync _|p, 0xffffffff;\n"
                    "@p mbarrier.arrive.expect_tx.shared::cta.b64 _, [%2], 7168;\n"
                    "@p cp.async.bulk.tensor.3d.shared::cluster.global.mbarrier::complete_tx::bytes.L2::cache_hint "
                    "[%0], [%1, {%3, %4, %3}], [%2], %5;\n}"
                    ::"r"(sbase + L::RING + ws * STAGE_BYTES + (k & 1) * SEG_BYTES), "l"(&p.wom[cta >> 6]), "r"(bar_wo + k * 8),
                      "r"(0), "r"(((h0 + (k >> 2)) & 7) * 512 + (sl0 + (k & 3)) * 8), "l"(pol) : "memory");
            }
        }
    } else if (warp == W + 1) {
        uint32_t tag;
        asm volatile("ld.relaxed.gpu.global.u32 %0, [%1];" : "=r"(tag) : "l"(&g_epoch) : "memory");
        tag += 1;
        auto wait_progress = [&](int target) {
            unsigned n = 0;
            while (s_tk[30] < target) {
                __nanosleep(100);
                if (++n > SPIN_LIMIT) __trap();
            }
        };
        {
            asm volatile("bar.sync 2, %0;" ::"n"(NTHREADS) : "memory");
            if (has_task) mbar_wait(bar_wqdone, 0); else mbar_wait(bar_fullv + (K0 - 1) * 8, 0);
#pragma unroll 1
            for (int h = 0; h < 16; h++) {
                if (h == 1) wait_progress(Q_DELAY);
                unsigned n = 0;
                uint32_t qa[4], qb[4];
                while (true) {
                    bool ok = true;
#pragma unroll
                    for (int i = 0; i < 4; i++) ok &= ll_load(g_q + h * 128 + i * 32 + lane, qa[i], qb[i], tag);
                    if (__all_sync(0xffffffffu, ok)) break;
                    if (++n > SPIN_LIMIT) __trap();
                }
#pragma unroll
                for (int i = 0; i < 4; i++) s_q0[h * 128 + i * 32 + lane] = make_uint2(qa[i], qb[i]);
                __syncwarp();
                if (lane == 0) {
                    if (h == 0) mbar_arrive(bar_q);
                    if (h == 3) mbar_arrive(bar_q2);
                    if (h == 15) mbar_arrive(bar_q3);
                }
            }
        }
        if (cta < 112) {
            const uint32_t bit = tag & 1u;
#pragma unroll 1
            for (int k = 0; k < 8; k++) {
                const int h = h0 + (k >> 2);
                wait_progress((h + 1) * 4096 + MERGE_DELAY);
                const uint32_t o2 = merge_slice(h, sl0 + (k & 3), bit, lane);
                if (lane < 4) s_ofin[k * 4 + lane] = o2;
            }
            __syncwarp();
            if (lane == 0) mbar_arrive(bar_ofin);
            wait_progress(TOTAL - XSTOP);
            const int cg = cta >= 56 ? cta - 56 : cta;
            const uint32_t bitmask = 0u - bit;
            const uint4* src = g_ol + (size_t)cta * 64 * 2 + lane;
            const int et = 2 * (lane & 1) + ((lane >> 1) & 1), es = (lane >> 2) & 1;
            const int col = (cta >= 56 ? DM : 0) + 64 * (cg >> 3) + 16 * et + 8 * es + (cg & 7);
            __nv_bfloat16* dst = p.out + col;
            unsigned n = 0;
            while (true) {
                uint4 v[4];
#pragma unroll
                for (int i = 0; i < 4; i++) ld2x64(v[i], src + i * 32);
                const uint32_t bad = or3(xor_or(v[0].x, v[0].z, bitmask), xor_or(v[1].x, v[1].z, bitmask),
                                         xor_or(v[2].x, v[2].z, bitmask)) | xor_or(v[3].x, v[3].z, bitmask);
                const bool done = __all_sync(0xffffffffu, (bad & 1u) == 0);
                const float a0 = (__uint_as_float(v[0].x) + __uint_as_float(v[1].x)) + (__uint_as_float(v[2].x) + __uint_as_float(v[3].x));
                const float a1 = (__uint_as_float(v[0].y) + __uint_as_float(v[1].y)) + (__uint_as_float(v[2].y) + __uint_as_float(v[3].y));
                const float a2 = (__uint_as_float(v[0].z) + __uint_as_float(v[1].z)) + (__uint_as_float(v[2].z) + __uint_as_float(v[3].z));
                const float a3 = (__uint_as_float(v[0].w) + __uint_as_float(v[1].w)) + (__uint_as_float(v[2].w) + __uint_as_float(v[3].w));
                if (done || n == 0) {
                    const bool u1 = lane & 2, u2 = lane & 4;
                    const float bx = (u1 ? a2 : a0) + __shfl_xor_sync(0xffffffffu, u1 ? a0 : a2, 2);
                    const float by = (u1 ? a3 : a1) + __shfl_xor_sync(0xffffffffu, u1 ? a1 : a3, 2);
                    float c = (u2 ? by : bx) + __shfl_xor_sync(0xffffffffu, u2 ? bx : by, 4);
                    c += __shfl_xor_sync(0xffffffffu, c, 8);
                    c += __shfl_xor_sync(0xffffffffu, c, 16);
                    if (done && lane < 8) *dst = __float2bfloat16(c);
                    if (done) break;
                    mbar_wait(bar_pub, 0);
                }
                if (++n > SPIN_LIMIT) __trap();
            }
        }
    } else {
        uint32_t tag;
        asm volatile("ld.relaxed.gpu.global.u32 %0, [%1];" : "=r"(tag) : "l"(&g_epoch) : "memory");
        const int g = lane >> 2, t4 = lane & 3;
        if (has_task) {
            const int tb = cta >> 6, qs = cta & 63;
            const int r = threadIdx.x >> 3, c8 = threadIdx.x & 7;
            const uint2* xp = reinterpret_cast<const uint2*>(p.x[tb] + 28 * r);
            uint2 xv[7];
#pragma unroll
            for (int i = 0; i < 7; i++)
                asm volatile("ld.global.nc.v2.u32 {%0,%1}, [%2];" : "=r"(xv[i].x), "=r"(xv[i].y) : "l"(xp + i));
            asm volatile("bar.sync 2, %0;" ::"n"(NTHREADS) : "memory");
            mbar_wait(bar_wq, 0);
            const uint4* wv = reinterpret_cast<const uint4*>(smem + L::RING + (NS - 4) * STAGE_BYTES) + 28 * r * 8 + c8;
            float acc[8];
#pragma unroll
            for (int j = 0; j < 8; j++) acc[j] = 0.f;
#pragma unroll
            for (int i = 0; i < 28; i++) {
                const uint32_t xw = (i & 2) ? xv[i >> 2].y : xv[i >> 2].x;
                const float xs = (i & 1) ? bf_hi(xw) : bf_lo(xw);
                const uint4 v = wv[i * 8];
                acc[0] += xs * bf_lo(v.x); acc[1] += xs * bf_hi(v.x);
                acc[2] += xs * bf_lo(v.y); acc[3] += xs * bf_hi(v.y);
                acc[4] += xs * bf_lo(v.z); acc[5] += xs * bf_hi(v.z);
                acc[6] += xs * bf_lo(v.w); acc[7] += xs * bf_hi(v.w);
            }
#pragma unroll
            for (int j = 0; j < 8; j++) {
                acc[j] += __shfl_xor_sync(0xffffffffu, acc[j], 8);
                acc[j] += __shfl_xor_sync(0xffffffffu, acc[j], 16);
            }
            if (lane < 8) {
                float4* d = reinterpret_cast<float4*>(s_red + warp * 64 + lane * 8);
                d[0] = make_float4(acc[0], acc[1], acc[2], acc[3]);
                d[1] = make_float4(acc[4], acc[5], acc[6], acc[7]);
            }
            asm volatile("bar.sync 1, %0;" ::"n"(W * 32) : "memory");
            if (threadIdx.x < 16) {
                const int il = threadIdx.x >> 2;
                float q[4];
#pragma unroll
                for (int k = 0; k < 4; k++) {
                    const int d = 16 * il + 2 * t4 + (k & 1) + 8 * (k >> 1);
                    q[k] = 0.f;
#pragma unroll
                    for (int w = 0; w < W; w++) q[k] += s_red[w * 64 + d];
                }
                ll_store(g_q + ((tb * 16 + (qs >> 2)) * 16 + (qs & 3) * 4 + il) * 4 + t4,
                         pack_bf16(q[0], q[1]), pack_bf16(q[2], q[3]), tag + 1);
            }
            __syncwarp();
            if (lane == 0) mbar_arrive(bar_wqdone);
        } else {
            asm volatile("bar.sync 2, %0;" ::"n"(NTHREADS) : "memory");
        }
        tag += 1;
        const uint32_t bit = tag & 1u;

        float acc[4][4];
#pragma unroll
        for (int i = 0; i < 4; i++) { acc[i][0] = 0.f; acc[i][1] = 0.f; acc[i][2] = 0.f; acc[i][3] = 0.f; }
        float m0 = -INFINITY, m1 = -INFINITY;
        float lacc[4] = {0.f, 0.f, 0.f, 0.f};
        const uint32_t ones[4] = {0x3f803f80u, 0x3f803f80u, 0x3f803f80u, 0x3f803f80u};
        uint32_t qf[16][2];
        int cur = 0;
        const uint32_t krow = (lane & 7) + 8 * ((lane >> 3) & 1), vrow = (lane & 7) + 8 * (lane >> 4);
        const uint32_t koff = krow * 128 + (((lane >> 4) ^ (krow & 7)) << 4);
        const uint32_t voff = TILE_BYTES + vrow * 128 + ((((lane >> 3) & 1) ^ (vrow & 7)) << 4);
        const float SC = 0.0625f * 1.4426950408889634f;
        char* const ydst = reinterpret_cast<char*>(g_ol + ((size_t)((cta >> 6) * 56 + 8 * warp + g) * 64 + (cta & 63)) * 2) + t4 * 8;
        int s = warp;
        uint32_t ph = 0;
        mbar_wait(bar_q, 0);
#pragma unroll
        for (int i = 0; i < 16; i++) {
            const uint2 v = s_q0[((g & 1) * 16 + i) * 4 + t4];
            qf[i][0] = v.x;
            qf[i][1] = v.y;
        }
        while (true) {
            mbar_wait(bar_full + s * 8, ph);
            const int t = s_tk[s];
            const int h = t >> 12;
            if (h != cur) {
                while (cur < h) {
                    float* sl = s_slots + warp * 2 * SLOT_STRIDE + 16 * t4 + 8 * (t4 >> 1) + g;
                    if (lane == 0) *reinterpret_cast<float4*>(s_slotml + warp * 4) = make_float4(m0, lacc[0], m1, lacc[1]);
#pragma unroll
                    for (int j = 0; j < 4; j++) {
                        sl[80 * j] = acc[j][0];
                        sl[80 * j + SLOT_STRIDE] = acc[j][1];
                        sl[80 * j + 8] = acc[j][2];
                        sl[80 * j + 8 + SLOT_STRIDE] = acc[j][3];
                    }
                    uint4* po = g_po + ((size_t)(cur * 16 + 4 * warp + (lane >> 3)) * G + cta) * 8 + (lane & 7);
                    asm volatile("bar.sync 1, %0;" ::"n"(W * 32) : "memory");
                    float2 mlw[W];
                    float4 sv[W];
                    float M = -INFINITY;
#pragma unroll
                    for (int w = 0; w < W; w++) {
                        mlw[w] = *reinterpret_cast<const float2*>(s_slotml + w * 4 + (warp & 2));
                        sv[w] = *reinterpret_cast<const float4*>(s_slots + (w * 2 + (warp >> 1)) * SLOT_STRIDE + 160 * (warp & 1) + 4 * lane + (lane & 24));
                        M = fmaxf(M, mlw[w].x);
                    }
                    const float R = (M == -INFINITY) ? 0.f : M;
                    float4 o = make_float4(0.f, 0.f, 0.f, 0.f);
                    float Lw = 0.f;
#pragma unroll
                    for (int w = 0; w < W; w++) {
                        const float f = ex2(mlw[w].x - R);
                        Lw += f * mlw[w].y;
                        o.x += f * sv[w].x; o.y += f * sv[w].y; o.z += f * sv[w].z; o.w += f * sv[w].w;
                    }
                    float inv, lg;
                    asm("rcp.approx.ftz.f32 %0, %1;" : "=f"(inv) : "f"(fmaxf(Lw, 1e-30f)));
                    asm("lg2.approx.ftz.f32 %0, %1;" : "=f"(lg) : "f"(Lw));
                    const uint32_t lse = pt_enc(fmaxf(M + lg, -3.0e38f), bit);
                    st128(po, __byte_perm(__float_as_uint(o.x * inv), lse, 0x3214), __byte_perm(__float_as_uint(o.y * inv), lse, 0x3215),
                          __byte_perm(__float_as_uint(o.z * inv), lse, 0x3216), __byte_perm(__float_as_uint(o.w * inv), lse, 0x3217));
                    if (cur == 13) {
                        st128(po + 2 * 128 * G, bit ^ 1u, 0u, 0u, 0u);
                        if (has_task) {
                            st64(ydst, bit ^ 1u, 0u);
                            if (warp < 3) st64(ydst + 4 * 8 * 64 * 32, bit ^ 1u, 0u);
                        }
                    }
#pragma unroll
                    for (int i = 0; i < 4; i++) { acc[i][0] = 0.f; acc[i][1] = 0.f; acc[i][2] = 0.f; acc[i][3] = 0.f; }
                    m0 = -INFINITY; m1 = -INFINITY;
                    lacc[0] = 0.f; lacc[1] = 0.f; lacc[2] = 0.f; lacc[3] = 0.f;
                    cur++;
                    asm volatile("bar.sync 1, %0;" ::"n"(W * 32) : "memory");
                }
                if (h >= 16) break;
                mbar_wait(h > 3 ? bar_q3 : bar_q2, 0);
#pragma unroll
                for (int i = 0; i < 16; i++) {
                    const uint2 v = s_q0[h * 128 + ((g & 1) * 16 + i) * 4 + t4];
                    qf[i][0] = v.x;
                    qf[i][1] = v.y;
                }
            }
            const uint32_t stage = sbase + L::RING + s * STAGE_BYTES;
            float sc[4][4];
#pragma unroll
            for (int c = 0; c < 4; c++) { sc[c][0] = 0.f; sc[c][1] = 0.f; sc[c][2] = 0.f; sc[c][3] = 0.f; }
            const uint32_t kb = stage + koff;
#pragma unroll
            for (int i = 0; i < 16; i++) {
                uint32_t a[4];
                ldsm4(a, (kb ^ ((i & 3) << 5)) + (i >> 2) * 2048);
                mma16816(sc[i & 3], a, qf[i][0], qf[i][1]);
            }
            const uint32_t r01 = pack_bf16((sc[0][0] + sc[1][0]) + (sc[2][0] + sc[3][0]), (sc[0][1] + sc[1][1]) + (sc[2][1] + sc[3][1]));
            const uint32_t r23 = pack_bf16((sc[0][2] + sc[1][2]) + (sc[2][2] + sc[3][2]), (sc[0][3] + sc[1][3]) + (sc[2][3] + sc[3][3]));
            const float s0 = bf_lo(r01) * SC, s1 = bf_hi(r01) * SC, s2 = bf_lo(r23) * SC, s3 = bf_hi(r23) * SC;
            float n0 = fmaxf(s0, s2), n1 = fmaxf(s1, s3);
            if (__any_sync(0xffffffffu, (n0 > m0) | (n1 > m1))) {
                n0 = fmaxf(warp_max(n0), m0);
                n1 = fmaxf(warp_max(n1), m1);
                const float f0 = ex2(m0 - n0), f1 = ex2(m1 - n1);
                m0 = n0; m1 = n1;
                lacc[0] *= f0; lacc[1] *= f1; lacc[2] *= f0; lacc[3] *= f1;
#pragma unroll
                for (int i = 0; i < 4; i++) { acc[i][0] *= f0; acc[i][1] *= f1; acc[i][2] *= f0; acc[i][3] *= f1; }
            }
            const float p0 = ex2(s0 - m0), p1 = ex2(s1 - m1), p2 = ex2(s2 - m0), p3 = ex2(s3 - m1);
            const uint32_t b0 = movtrans(pack_bf16(p0, p1));
            const uint32_t b1 = movtrans(pack_bf16(p2, p3));
            mbar_wait(bar_fullv + s * 8, ph);
            const uint32_t vb = stage + voff;
#pragma unroll
            for (int q = 0; q < 4; q++) {
                const uint32_t c0 = ((g >> 1) == q) ? b0 : 0u, c1 = ((g >> 1) == q) ? b1 : 0u;
#pragma unroll
                for (int j = 0; j < 4; j++) {
                    uint32_t a[4];
                    ldsm4t(a, (vb ^ (q << 5)) + j * 2048);
                    mma16816(acc[j], a, c0, c1);
                }
            }
            mma16816(lacc, ones, b0, b1);
            __syncwarp();
            if (lane == 0) mbar_arrive(bar_empty + s * 8);
            s += W;
            if (s >= NS) { s -= NS; ph ^= 1; }
        }

        if (has_task) {
            if (!isX) mbar_wait(bar_ofin, 0);
            float y[7][4];
#pragma unroll
            for (int j = 0; j < 7; j++) { y[j][0] = 0.f; y[j][1] = 0.f; y[j][2] = 0.f; y[j][3] = 0.f; }
            float2* red = reinterpret_cast<float2*>(s_red);
#pragma unroll 1
            for (int k = warp; k < 8; k += W) {
                int ws = s_tk[31] + (k >> 1);
                if (ws >= NS) ws -= NS;
                mbar_wait(bar_wo + k * 8, 0);
                uint32_t wf[14][4];
                load_wo_frags(wf, sbase + L::RING + ws * STAGE_BYTES + (k & 1) * SEG_BYTES, lane);
                uint32_t o2;
                if (isX) o2 = merge_slice(14 + (k >> 2), sl0 + warp, bit, lane);
                else o2 = s_ofin[k * 4 + t4];
                project(y, wf, o2, lane);
                if (k >= W || isX) {
                    const uint32_t obit = (k >= W) ? bit : bit ^ 1u;
#pragma unroll
                    for (int j = 0; j < 7; j++) red[(warp * 7 + j) * 32 + lane] = make_float2(y[j][0], y[j][2]);
                    asm volatile("bar.sync 1, %0;" ::"n"(W * 32) : "memory");
#pragma unroll
                    for (int jj = 0; jj < 2; jj++) {
                        const int j = warp + 4 * jj;
                        if (j < 7) {
                            float vx = 0.f, vy = 0.f;
#pragma unroll
                            for (int w = 0; w < W; w++) {
                                const float2 v = red[(w * 7 + j) * 32 + lane];
                                vx += v.x;
                                vy += v.y;
                            }
                            st64(ydst + jj * 4 * 8 * 64 * 32, pt_enc(vx, obit), __float_as_uint(vy));
                        }
                    }
                    if (k < W) asm volatile("bar.sync 1, %0;" ::"n"(W * 32) : "memory");
                }
            }
            if (lane == 0) mbar_arrive(bar_pub);
            if (cta == 127 && threadIdx.x == 0) {
                asm volatile("st.relaxed.gpu.global.u32 [%0], %1;" ::"l"(&g_ticket), "r"(0u) : "memory");
                asm volatile("st.relaxed.gpu.global.u32 [%0], %1;" ::"l"(&g_epoch), "r"(tag) : "memory");
            }
        }
    }
}

constexpr int FB_SPLIT = 32;
__device__ float g_fq[2 * 4096];
__device__ float g_fp[16 * FB_SPLIT * 8 * 2 * 264];

__global__ void fb_q_kernel(const __nv_bfloat16* x, const __nv_bfloat16* wq, int b) {
    const int n = blockIdx.x * blockDim.x + threadIdx.x;
    float a = 0.f;
    for (int k = 0; k < DM; k++) a += __bfloat162float(x[k]) * __bfloat162float(wq[(size_t)k * 4096 + n]);
    g_fq[b * 4096 + n] = __bfloat162float(__float2bfloat16(a));
}
__global__ void fb_attn_kernel(const uint4* k, const uint4* v, int b) {
    const int hk = blockIdx.y, warp = threadIdx.x >> 5, lane = threadIdx.x & 31;
    float q[2][8], o[2][8], m[2] = {-INFINITY, -INFINITY}, l[2] = {0.f, 0.f};
    for (int h = 0; h < 2; h++)
        for (int j = 0; j < 8; j++) { q[h][j] = g_fq[b * 4096 + (hk * 2 + h) * 256 + lane * 8 + j]; o[h][j] = 0.f; }
    const int n = 65536 / FB_SPLIT / 8;
    const size_t row0 = (size_t)hk * 65536 + (size_t)(blockIdx.x * 8 + warp) * n;
    for (int i = 0; i < n; i++) {
        const uint4 kk = k[(row0 + i) * 32 + lane], vv = v[(row0 + i) * 32 + lane];
        const float kf[8] = {bf_lo(kk.x), bf_hi(kk.x), bf_lo(kk.y), bf_hi(kk.y), bf_lo(kk.z), bf_hi(kk.z), bf_lo(kk.w), bf_hi(kk.w)};
        const float vf[8] = {bf_lo(vv.x), bf_hi(vv.x), bf_lo(vv.y), bf_hi(vv.y), bf_lo(vv.z), bf_hi(vv.z), bf_lo(vv.w), bf_hi(vv.w)};
#pragma unroll
        for (int h = 0; h < 2; h++) {
            float s = 0.f;
#pragma unroll
            for (int j = 0; j < 8; j++) s += q[h][j] * kf[j];
            for (int d = 16; d >= 1; d >>= 1) s += __shfl_xor_sync(0xffffffffu, s, d);
            s = __bfloat162float(__float2bfloat16(s)) * (0.0625f * 1.4426950408889634f);
            const float mn = fmaxf(m[h], s), f = ex2(m[h] - mn), pr = ex2(s - mn);
            m[h] = mn;
            l[h] = l[h] * f + pr;
#pragma unroll
            for (int j = 0; j < 8; j++) o[h][j] = o[h][j] * f + pr * vf[j];
        }
    }
    for (int h = 0; h < 2; h++) {
        float* d = g_fp + ((((size_t)(b * 8 + hk) * FB_SPLIT + blockIdx.x) * 8 + warp) * 2 + h) * 264;
        for (int j = 0; j < 8; j++) d[lane * 8 + j] = o[h][j];
        if (lane == 0) { d[256] = m[h]; d[257] = l[h]; }
    }
}
__global__ void fb_merge_kernel() {
    const int hq = blockIdx.x;
    const float* base = g_fp + ((size_t)(hq >> 1) * FB_SPLIT * 8 * 2 + (hq & 1)) * 264;
    float M = -INFINITY, Ls = 0.f, a = 0.f;
    for (int i = 0; i < FB_SPLIT * 8; i++) M = fmaxf(M, base[(size_t)i * 528 + 256]);
    for (int i = 0; i < FB_SPLIT * 8; i++) {
        const float w = ex2(base[(size_t)i * 528 + 256] - M);
        Ls += w * base[(size_t)i * 528 + 257];
        a += w * base[(size_t)i * 528 + threadIdx.x];
    }
    g_fq[hq * 256 + threadIdx.x] = __bfloat162float(__float2bfloat16(a / Ls));
}
__global__ void fb_out_kernel(const __nv_bfloat16* wo, __nv_bfloat16* out, int b) {
    const int n = blockIdx.x * 64 + threadIdx.x;
    float a = 0.f;
    for (int k = 0; k < 4096; k++) a += g_fq[b * 4096 + k] * __bfloat162float(wo[(size_t)k * DM + n]);
    out[b * DM + n] = __float2bfloat16(a);
}

typedef CUresult (*EncodeFn)(CUtensorMap*, CUtensorMapDataType, cuuint32_t, void*, const cuuint64_t*, const cuuint64_t*,
                             const cuuint32_t*, const cuuint32_t*, CUtensorMapInterleave, CUtensorMapSwizzle,
                             CUtensorMapL2promotion, CUtensorMapFloatOOBfill);

void encode_kv(EncodeFn enc, CUtensorMap* m, const void* ptr) {
    cuuint64_t gd[3] = {64, 8ull * 65536ull, 4};
    cuuint64_t gs[2] = {512, 128};
    cuuint32_t box[3] = {64, 16, 4};
    cuuint32_t es[3] = {1, 1, 1};
    enc(m, CU_TENSOR_MAP_DATA_TYPE_BFLOAT16, 3, const_cast<void*>(ptr), gd, gs, box, es, CU_TENSOR_MAP_INTERLEAVE_NONE,
        CU_TENSOR_MAP_SWIZZLE_128B, CU_TENSOR_MAP_L2_PROMOTION_L2_256B, CU_TENSOR_MAP_FLOAT_OOB_FILL_NONE);
}

void encode_wo(EncodeFn enc, CUtensorMap* m, const void* ptr) {
    cuuint64_t gd[3] = {64, 4096, 7};
    cuuint64_t gs[2] = {DM * 2, 128};
    cuuint32_t box[3] = {64, 8, 7};
    cuuint32_t es[3] = {1, 1, 1};
    enc(m, CU_TENSOR_MAP_DATA_TYPE_BFLOAT16, 3, const_cast<void*>(ptr), gd, gs, box, es, CU_TENSOR_MAP_INTERLEAVE_NONE,
        CU_TENSOR_MAP_SWIZZLE_128B, CU_TENSOR_MAP_L2_PROMOTION_L2_128B, CU_TENSOR_MAP_FLOAT_OOB_FILL_NONE);
}

void encode_wq(EncodeFn enc, CUtensorMap* m, const void* ptr) {
    cuuint64_t gd[2] = {4096, 448};
    cuuint64_t gs[1] = {8192};
    cuuint32_t box[2] = {64, 224};
    cuuint32_t es[2] = {1, 1};
    enc(m, CU_TENSOR_MAP_DATA_TYPE_BFLOAT16, 2, const_cast<void*>(ptr), gd, gs, box, es, CU_TENSOR_MAP_INTERLEAVE_NONE,
        CU_TENSOR_MAP_SWIZZLE_NONE, CU_TENSOR_MAP_L2_PROMOTION_L2_128B, CU_TENSOR_MAP_FLOAT_OOB_FILL_NONE);
}

}

extern "C" void kernel_launch(void* const* d_in, const int* in_sizes, int n_in, void* d_out, int out_size) {
    (void)in_sizes; (void)n_in; (void)out_size;
    static EncodeFn enc = nullptr;
    static int mode = -1;
    if (mode < 0) {
        cudaDriverEntryPointQueryResult qr;
        void* fn = nullptr;
        cudaGetDriverEntryPoint("cuTensorMapEncodeTiled", &fn, cudaEnableDefault, &qr);
        enc = (EncodeFn)fn;
        int dev = 0, sms = 0, occ = 0;
        cudaGetDevice(&dev);
        cudaDeviceGetAttribute(&sms, cudaDevAttrMultiProcessorCount, dev);
        const bool attr_ok =
            cudaFuncSetAttribute(fused_decode_kernel, cudaFuncAttributeMaxDynamicSharedMemorySize, L::SIZE) == cudaSuccess;
        if (attr_ok) cudaOccupancyMaxActiveBlocksPerMultiprocessor(&occ, fused_decode_kernel, NTHREADS, L::SIZE);
        mode = (enc != nullptr && attr_ok && sms * occ >= G) ? 1 : 0;
        (void)cudaGetLastError();
    }
    if (mode == 1) {
        Params p;
        for (int b = 0; b < 2; b++) {
            p.x[b] = (const __nv_bfloat16*)d_in[5 * b + 0];
            encode_kv(enc, &p.km[b], d_in[5 * b + 1]);
            encode_kv(enc, &p.vm[b], d_in[5 * b + 2]);
            encode_wq(enc, &p.wqm[b], d_in[5 * b + 3]);
            encode_wo(enc, &p.wom[b], d_in[5 * b + 4]);
        }
        p.out = (__nv_bfloat16*)d_out;
        fused_decode_kernel<<<G, NTHREADS, L::SIZE>>>(p);
    } else {
        for (int b = 0; b < 2; b++) {
            fb_q_kernel<<<16, 256>>>((const __nv_bfloat16*)d_in[5 * b], (const __nv_bfloat16*)d_in[5 * b + 3], b);
            fb_attn_kernel<<<dim3(FB_SPLIT, 8), 256>>>((const uint4*)d_in[5 * b + 1], (const uint4*)d_in[5 * b + 2], b);
        }
        fb_merge_kernel<<<32, 256>>>();
        for (int b = 0; b < 2; b++)
            fb_out_kernel<<<7, 64>>>((const __nv_bfloat16*)d_in[5 * b + 4], (__nv_bfloat16*)d_out, b);
    }
}
```
